```python
import torch

def _softmax(x, axis=-1):
    return torch.softmax(x, dim=axis)
def _gelu(x):
    return torch.nn.functional.gelu(x, approximate="tanh")
def _silu(x):
    return torch.nn.functional.silu(x)
def _sigmoid(x):
    return torch.sigmoid(x)
def _layernorm(x, axis=-1, eps=1e-5):
    m = x.mean(dim=axis, keepdim=True)
    v = x.var(dim=axis, keepdim=True, unbiased=False)
    return (x - m) / torch.sqrt(v + eps)
def _scatter_add(tgt, idx, src, axis=0):
    return tgt.clone().index_add_(axis, idx, src)
def _segment_sum(src, seg, n):
    out = torch.zeros((n,) + src.shape[1:], dtype=src.dtype)
    return out.index_add_(0, seg, src)
def _pad(x, pw):
    flat = tuple(v for pair in reversed(pw) for v in pair)
    return torch.nn.functional.pad(x, flat)

kernel_name = 'gated_mix__ssm_conv_h3__glu_gated_geglu__prompt'

def setup_inputs():

    _w = (lambda a: (lambda t: t.to(torch.bfloat16) if t.is_floating_point() else t)(torch.as_tensor(a)))
    def _A_setup():
        B, S, D = 1, 2048, 640
        ks = 4
        return {
            "q": _w((lambda *s: torch.randn(*s, dtype=torch.bfloat16) * 0.05)(B, S, D)),
            "k": _w((lambda *s: torch.randn(*s, dtype=torch.bfloat16) * 0.05)(B, S, D)),
            "v": _w((lambda *s: torch.randn(*s, dtype=torch.bfloat16) * 0.05)(B, S, D)),
            "shift_k": _w((lambda *s: torch.randn(*s, dtype=torch.bfloat16) * 0.05)(D, ks) * 0.5),
            "ssm_k": _w((lambda *s: torch.randn(*s, dtype=torch.bfloat16) * 0.05)(D, S) * (1.0 / S ** 0.5)),
            "ssm_D": _w((lambda *s: torch.randn(*s, dtype=torch.bfloat16) * 0.05)(D)),
        }
    _A_in = _A_setup()

    def _B_setup():
        B, S, Dm, Df = 1, 2048, 640, 1728
        return {
            "x": _w((lambda *s: torch.randn(*s, dtype=torch.bfloat16) * 0.05)(B, S, Dm)),
            "w_gate": _w((lambda *s: torch.randn(*s, dtype=torch.bfloat16) * 0.1)(Dm, Df) * (Dm ** -0.5)),
            "w_up": _w((lambda *s: torch.randn(*s, dtype=torch.bfloat16) * 0.1)(Dm, Df) * (Dm ** -0.5)),
            "w_down": _w((lambda *s: torch.randn(*s, dtype=torch.bfloat16) * 0.1)(Df, Dm) * (Df ** -0.5)),
        }
    _B_in = _B_setup()

    return {
        "A_q": _A_in["q"],
        "A_k": _A_in["k"],
        "A_v": _A_in["v"],
        "A_shift_k": _A_in["shift_k"],
        "A_ssm_k": _A_in["ssm_k"],
        "A_ssm_D": _A_in["ssm_D"],
        "B_x": _B_in["x"],
        "B_w_gate": _B_in["w_gate"],
        "B_w_up": _B_in["w_up"],
        "B_w_down": _B_in["w_down"],
        "gate_w": _w((lambda *s: torch.randn(*s, dtype=torch.bfloat16) * 0.05)(640) * 16.0),
    }

def reference(A_q, A_k, A_v, A_shift_k, A_ssm_k, A_ssm_D, B_x, B_w_gate, B_w_up, B_w_down, gate_w):
    def _A_ref(q, k, v, shift_k, ssm_k, ssm_D):
        B, S, D = q.shape
        ks = shift_k.shape[-1]
        k_pad = _pad(k, ((0, 0), (ks - 1, 0), (0, 0)))
        k_shift = torch.zeros_like(k)
        for t in range(ks):
            k_shift = k_shift + k_pad[:, t:t + S, :] * shift_k[:, ks - 1 - t][None, None, :]
        kv = k_shift * v
        L = 2 * S
        kv_pad = _pad(kv, ((0, 0), (0, S), (0, 0)))
        kf_pad = _pad(ssm_k, ((0, 0), (0, S)))
        kv_f = (lambda x, axes=(-2,-1): torch.fft.rfft2(x.float(), dim=axes))(kv_pad[:, None, :, :], axes=(1, 2))
        kf_f = (lambda x, axes=(-2,-1): torch.fft.rfft2(x.float(), dim=axes))(kf_pad[:, None, :], axes=(1, 2))
        kf_f = (lambda x, *d: x.permute(*d))(kf_f, 1, 2, 0)
        y_f = kv_f * kf_f[None, :, :, :]
        y = (lambda x, s, axes=(-2,-1): torch.fft.irfft2(x, s=s, dim=axes).to(torch.bfloat16))(y_f, (1, L), axes=(1, 2))[:, 0, :S, :]
        y = y + kv * ssm_D[None, None, :]
        return q * y

    def _B_ref(x, w_gate, w_up, w_down):
        g = torch.einsum("bsd,df->bsf", x, w_gate)
        u = torch.einsum("bsd,df->bsf", x, w_up)
        h = _gelu(g) * u
        return torch.einsum("bsf,fd->bsd", h, w_down)

    x = A_q
    g = _sigmoid((x * gate_w).sum(-1, keepdims=True))
    a = _A_ref(x, A_k, A_v, A_shift_k, A_ssm_k, A_ssm_D)
    b = _B_ref(x, B_w_gate, B_w_up, B_w_down)
    return g * a + (1 - g) * b
```

```cpp
#include <cuda_runtime.h>
#include <cuda.h>
#include <cuda_bf16.h>
#include <stdint.h>

typedef __nv_bfloat16 bf16;
constexpr int SEQ = 2048, DM = 640, DF = 1728;

__device__ __align__(1024) bf16 g_h[SEQ * DF];
__device__ __align__(1024) bf16 g_kvT[DM * SEQ];
__device__ __align__(1024) bf16 g_zT[DM * SEQ];
__device__ float g_gate[SEQ];
constexpr int C_KV = 0, C_G = 8, C_H1 = 24, C_H2 = 40, C_Z = 56, C_DONE = 64, C_NUM = 65;
__device__ unsigned g_cnt[C_NUM * 32];
#define PROF(i)

constexpr int ST1 = 49152, NST1 = 4;
constexpr int ST2 = 26624, NST2 = 7;
constexpr int RING = ST1 * NST1;
constexpr int CB_HB = 128, CB_HA = 4288, CB_P0 = 8576, CB_PS = 2176, CB = 12800;
constexpr int OFF_CB = RING;
constexpr int OFF_STG = OFF_CB + 2 * CB;
constexpr int OFF_BAR = OFF_STG + 4224;
constexpr int SMEM_TOTAL = OFF_BAR + 256 + 1024;
constexpr int B_FULL1 = 0, B_EMPTY1 = 4, B_FULL2 = 8, B_EMPTY2 = 15, B_CFULL = 22, B_CDONE = 24, B_STG = 26, B_GO0 = 27, B_GO1 = 28, B_CRAW = 29, B_HD = 31;
constexpr int NCH = 5;
#define GATE0 0
#define GATE1 2

__device__ __forceinline__ void wgmma_ss_n128(float* d, uint64_t da, uint64_t db, int sd) {
    asm volatile("{\n.reg .pred p;\nsetp.ne.b32 p, %66, 0;\nwgmma.mma_async.sync.aligned.m64n128k16.f32.bf16.bf16 {%0,%1,%2,%3,%4,%5,%6,%7,%8,%9,%10,%11,%12,%13,%14,%15,%16,%17,%18,%19,%20,%21,%22,%23,%24,%25,%26,%27,%28,%29,%30,%31,%32,%33,%34,%35,%36,%37,%38,%39,%40,%41,%42,%43,%44,%45,%46,%47,%48,%49,%50,%51,%52,%53,%54,%55,%56,%57,%58,%59,%60,%61,%62,%63}, %64, %65, p, 1, 1, 0, 1;\n}\n"
    : "+f"(d[0]),"+f"(d[1]),"+f"(d[2]),"+f"(d[3]),"+f"(d[4]),"+f"(d[5]),"+f"(d[6]),"+f"(d[7]),"+f"(d[8]),"+f"(d[9]),"+f"(d[10]),"+f"(d[11]),"+f"(d[12]),"+f"(d[13]),"+f"(d[14]),"+f"(d[15]),"+f"(d[16]),"+f"(d[17]),"+f"(d[18]),"+f"(d[19]),"+f"(d[20]),"+f"(d[21]),"+f"(d[22]),"+f"(d[23]),"+f"(d[24]),"+f"(d[25]),"+f"(d[26]),"+f"(d[27]),"+f"(d[28]),"+f"(d[29]),"+f"(d[30]),"+f"(d[31]),"+f"(d[32]),"+f"(d[33]),"+f"(d[34]),"+f"(d[35]),"+f"(d[36]),"+f"(d[37]),"+f"(d[38]),"+f"(d[39]),"+f"(d[40]),"+f"(d[41]),"+f"(d[42]),"+f"(d[43]),"+f"(d[44]),"+f"(d[45]),"+f"(d[46]),"+f"(d[47]),"+f"(d[48]),"+f"(d[49]),"+f"(d[50]),"+f"(d[51]),"+f"(d[52]),"+f"(d[53]),"+f"(d[54]),"+f"(d[55]),"+f"(d[56]),"+f"(d[57]),"+f"(d[58]),"+f"(d[59]),"+f"(d[60]),"+f"(d[61]),"+f"(d[62]),"+f"(d[63]) : "l"(da), "l"(db), "r"(sd));
}
__device__ __forceinline__ void wgmma_ss_n96(float* d, uint64_t da, uint64_t db, int sd) {
    asm volatile("{\n.reg .pred p;\nsetp.ne.b32 p, %50, 0;\nwgmma.mma_async.sync.aligned.m64n96k16.f32.bf16.bf16 {%0,%1,%2,%3,%4,%5,%6,%7,%8,%9,%10,%11,%12,%13,%14,%15,%16,%17,%18,%19,%20,%21,%22,%23,%24,%25,%26,%27,%28,%29,%30,%31,%32,%33,%34,%35,%36,%37,%38,%39,%40,%41,%42,%43,%44,%45,%46,%47}, %48, %49, p, 1, 1, 0, 1;\n}\n"
    : "+f"(d[0]),"+f"(d[1]),"+f"(d[2]),"+f"(d[3]),"+f"(d[4]),"+f"(d[5]),"+f"(d[6]),"+f"(d[7]),"+f"(d[8]),"+f"(d[9]),"+f"(d[10]),"+f"(d[11]),"+f"(d[12]),"+f"(d[13]),"+f"(d[14]),"+f"(d[15]),"+f"(d[16]),"+f"(d[17]),"+f"(d[18]),"+f"(d[19]),"+f"(d[20]),"+f"(d[21]),"+f"(d[22]),"+f"(d[23]),"+f"(d[24]),"+f"(d[25]),"+f"(d[26]),"+f"(d[27]),"+f"(d[28]),"+f"(d[29]),"+f"(d[30]),"+f"(d[31]),"+f"(d[32]),"+f"(d[33]),"+f"(d[34]),"+f"(d[35]),"+f"(d[36]),"+f"(d[37]),"+f"(d[38]),"+f"(d[39]),"+f"(d[40]),"+f"(d[41]),"+f"(d[42]),"+f"(d[43]),"+f"(d[44]),"+f"(d[45]),"+f"(d[46]),"+f"(d[47]) : "l"(da), "l"(db), "r"(sd));
}
__device__ __forceinline__ void wgmma_ss_n80(float* d, uint64_t da, uint64_t db, int sd) {
    asm volatile("{\n.reg .pred p;\nsetp.ne.b32 p, %42, 0;\nwgmma.mma_async.sync.aligned.m64n80k16.f32.bf16.bf16 {%0,%1,%2,%3,%4,%5,%6,%7,%8,%9,%10,%11,%12,%13,%14,%15,%16,%17,%18,%19,%20,%21,%22,%23,%24,%25,%26,%27,%28,%29,%30,%31,%32,%33,%34,%35,%36,%37,%38,%39}, %40, %41, p, 1, 1, 0, 1;\n}\n"
    : "+f"(d[0]),"+f"(d[1]),"+f"(d[2]),"+f"(d[3]),"+f"(d[4]),"+f"(d[5]),"+f"(d[6]),"+f"(d[7]),"+f"(d[8]),"+f"(d[9]),"+f"(d[10]),"+f"(d[11]),"+f"(d[12]),"+f"(d[13]),"+f"(d[14]),"+f"(d[15]),"+f"(d[16]),"+f"(d[17]),"+f"(d[18]),"+f"(d[19]),"+f"(d[20]),"+f"(d[21]),"+f"(d[22]),"+f"(d[23]),"+f"(d[24]),"+f"(d[25]),"+f"(d[26]),"+f"(d[27]),"+f"(d[28]),"+f"(d[29]),"+f"(d[30]),"+f"(d[31]),"+f"(d[32]),"+f"(d[33]),"+f"(d[34]),"+f"(d[35]),"+f"(d[36]),"+f"(d[37]),"+f"(d[38]),"+f"(d[39]) : "l"(da), "l"(db), "r"(sd));
}
__device__ __forceinline__ void wgmma_ss_n32(float* d, uint64_t da, uint64_t db, int sd) {
    asm volatile("{\n.reg .pred p;\nsetp.ne.b32 p, %18, 0;\nwgmma.mma_async.sync.aligned.m64n32k16.f32.bf16.bf16 {%0,%1,%2,%3,%4,%5,%6,%7,%8,%9,%10,%11,%12,%13,%14,%15}, %16, %17, p, 1, 1, 0, 1;\n}\n"
    : "+f"(d[0]),"+f"(d[1]),"+f"(d[2]),"+f"(d[3]),"+f"(d[4]),"+f"(d[5]),"+f"(d[6]),"+f"(d[7]),"+f"(d[8]),"+f"(d[9]),"+f"(d[10]),"+f"(d[11]),"+f"(d[12]),"+f"(d[13]),"+f"(d[14]),"+f"(d[15]) : "l"(da), "l"(db), "r"(sd));
}
template<int SD> __device__ __forceinline__ void wgmma_rs_n16(float* d, const uint32_t* a, uint64_t db) {
    asm volatile("wgmma.mma_async.sync.aligned.m64n16k16.f32.bf16.bf16 {%0,%1,%2,%3,%4,%5,%6,%7}, {%8,%9,%10,%11}, %12, %13, 1, 1, 0;\n"
    : "+f"(d[0]),"+f"(d[1]),"+f"(d[2]),"+f"(d[3]),"+f"(d[4]),"+f"(d[5]),"+f"(d[6]),"+f"(d[7]) : "r"(a[0]), "r"(a[1]), "r"(a[2]), "r"(a[3]), "l"(db), "n"(SD));
}
template<int SD> __device__ __forceinline__ void wgmma_rs_n32(float* d, const uint32_t* a, uint64_t db) {
    asm volatile("wgmma.mma_async.sync.aligned.m64n32k16.f32.bf16.bf16 {%0,%1,%2,%3,%4,%5,%6,%7,%8,%9,%10,%11,%12,%13,%14,%15}, {%16,%17,%18,%19}, %20, %21, 1, 1, 0;\n"
    : "+f"(d[0]),"+f"(d[1]),"+f"(d[2]),"+f"(d[3]),"+f"(d[4]),"+f"(d[5]),"+f"(d[6]),"+f"(d[7]),"+f"(d[8]),"+f"(d[9]),"+f"(d[10]),"+f"(d[11]),"+f"(d[12]),"+f"(d[13]),"+f"(d[14]),"+f"(d[15]) : "r"(a[0]), "r"(a[1]), "r"(a[2]), "r"(a[3]), "l"(db), "n"(SD));
}
template<int SD> __device__ __forceinline__ void wgmma_rs_n48(float* d, const uint32_t* a, uint64_t db) {
    asm volatile("wgmma.mma_async.sync.aligned.m64n48k16.f32.bf16.bf16 {%0,%1,%2,%3,%4,%5,%6,%7,%8,%9,%10,%11,%12,%13,%14,%15,%16,%17,%18,%19,%20,%21,%22,%23}, {%24,%25,%26,%27}, %28, %29, 1, 1, 0;\n"
    : "+f"(d[0]),"+f"(d[1]),"+f"(d[2]),"+f"(d[3]),"+f"(d[4]),"+f"(d[5]),"+f"(d[6]),"+f"(d[7]),"+f"(d[8]),"+f"(d[9]),"+f"(d[10]),"+f"(d[11]),"+f"(d[12]),"+f"(d[13]),"+f"(d[14]),"+f"(d[15]),"+f"(d[16]),"+f"(d[17]),"+f"(d[18]),"+f"(d[19]),"+f"(d[20]),"+f"(d[21]),"+f"(d[22]),"+f"(d[23]) : "r"(a[0]), "r"(a[1]), "r"(a[2]), "r"(a[3]), "l"(db), "n"(SD));
}
template<int SD> __device__ __forceinline__ void wgmma_rs_n64(float* d, const uint32_t* a, uint64_t db) {
    asm volatile("wgmma.mma_async.sync.aligned.m64n64k16.f32.bf16.bf16 {%0,%1,%2,%3,%4,%5,%6,%7,%8,%9,%10,%11,%12,%13,%14,%15,%16,%17,%18,%19,%20,%21,%22,%23,%24,%25,%26,%27,%28,%29,%30,%31}, {%32,%33,%34,%35}, %36, %37, 1, 1, 0;\n"
    : "+f"(d[0]),"+f"(d[1]),"+f"(d[2]),"+f"(d[3]),"+f"(d[4]),"+f"(d[5]),"+f"(d[6]),"+f"(d[7]),"+f"(d[8]),"+f"(d[9]),"+f"(d[10]),"+f"(d[11]),"+f"(d[12]),"+f"(d[13]),"+f"(d[14]),"+f"(d[15]),"+f"(d[16]),"+f"(d[17]),"+f"(d[18]),"+f"(d[19]),"+f"(d[20]),"+f"(d[21]),"+f"(d[22]),"+f"(d[23]),"+f"(d[24]),"+f"(d[25]),"+f"(d[26]),"+f"(d[27]),"+f"(d[28]),"+f"(d[29]),"+f"(d[30]),"+f"(d[31]) : "r"(a[0]), "r"(a[1]), "r"(a[2]), "r"(a[3]), "l"(db), "n"(SD));
}
template<int N, int SD> __device__ __forceinline__ void wgmma_rs(float* d, const uint32_t* a, uint64_t db) {
    if constexpr (N == 16) wgmma_rs_n16<SD>(d, a, db);
    if constexpr (N == 32) wgmma_rs_n32<SD>(d, a, db);
    if constexpr (N == 48) wgmma_rs_n48<SD>(d, a, db);
    if constexpr (N == 64) wgmma_rs_n64<SD>(d, a, db);
}

__device__ __forceinline__ uint64_t make_desc(uint32_t saddr, uint32_t lbo, uint32_t sbo, uint32_t swz) {
    uint64_t d = 0;
    d |= (uint64_t)((saddr & 0x3FFFF) >> 4);
    d |= (uint64_t)((lbo & 0x3FFFF) >> 4) << 16;
    d |= (uint64_t)((sbo & 0x3FFFF) >> 4) << 32;
    d |= (uint64_t)swz << 62;
    return d;
}
#define WG_FENCE() asm volatile("wgmma.fence.sync.aligned;\n" ::: "memory")
#define WG_COMMIT() asm volatile("wgmma.commit_group.sync.aligned;\n" ::: "memory")
#define WG_WAIT(n) asm volatile("wgmma.wait_group.sync.aligned %0;\n" :: "n"(n) : "memory")
#define FENCE_ASYNC_S() asm volatile("fence.proxy.async.shared::cta;\n" ::: "memory")
#define FENCE_ASYNC_G() asm volatile("fence.proxy.async.global;\n" ::: "memory")

__device__ __forceinline__ void mbar_init(uint32_t bar, uint32_t cnt) { asm volatile("mbarrier.init.shared::cta.b64 [%0], %1;" :: "r"(bar), "r"(cnt)); }
__device__ __forceinline__ void mbar_expect_tx(uint32_t bar, uint32_t bytes) { asm volatile("mbarrier.arrive.expect_tx.shared::cta.b64 _, [%0], %1;" :: "r"(bar), "r"(bytes) : "memory"); }
__device__ __forceinline__ void mbar_arrive(uint32_t bar) { asm volatile("mbarrier.arrive.shared::cta.b64 _, [%0];" :: "r"(bar) : "memory"); }
__device__ __forceinline__ bool mbar_try(uint32_t bar, uint32_t parity) {
    uint32_t ok;
    asm volatile("{\n.reg .pred p;\nmbarrier.try_wait.parity.shared::cta.b64 p, [%1], %2;\nselp.u32 %0, 1, 0, p;\n}\n" : "=r"(ok) : "r"(bar), "r"(parity) : "memory");
    return ok != 0;
}
__device__ __forceinline__ void mbar_wait(uint32_t bar, uint32_t parity) {
    if (mbar_try(bar, parity)) return;
    if (mbar_try(bar, parity)) return;
    long long t0 = clock64();
    while (!mbar_try(bar, parity)) { if (clock64() - t0 > 100000000LL) break; }
}
__device__ __forceinline__ void mbar_arrive_cluster(uint32_t bar, uint32_t cta) {
    asm volatile("{\n.reg .b32 ra;\nmapa.shared::cluster.u32 ra, %0, %1;\nmbarrier.arrive.shared::cluster.b64 _, [ra];\n}\n" :: "r"(bar), "r"(cta) : "memory");
}
__device__ __forceinline__ void tma2d(uint32_t dst, const CUtensorMap* tm, int c0, int c1, uint32_t bar) {
    asm volatile("cp.async.bulk.tensor.2d.shared::cluster.global.mbarrier::complete_tx::bytes [%0], [%1, {%3, %4}], [%2];"
        :: "r"(dst), "l"(tm), "r"(bar), "r"(c0), "r"(c1) : "memory");
}
__device__ __forceinline__ void tma2d_mc(uint32_t dst, const CUtensorMap* tm, int c0, int c1, uint32_t bar) {
    asm volatile("cp.async.bulk.tensor.2d.shared::cluster.global.mbarrier::complete_tx::bytes.multicast::cluster [%0], [%1, {%3, %4}], [%2], %5;"
        :: "r"(dst), "l"(tm), "r"(bar), "r"(c0), "r"(c1), "h"((uint16_t)3) : "memory");
}
__device__ __forceinline__ void tma5d(uint32_t dst, const CUtensorMap* tm, int c2, int c4, uint32_t bar) {
    asm volatile("cp.async.bulk.tensor.5d.shared::cluster.global.mbarrier::complete_tx::bytes [%0], [%1, {%3, %3, %4, %3, %5}], [%2];"
        :: "r"(dst), "l"(tm), "r"(bar), "r"(0), "r"(c2), "r"(c4) : "memory");
}
__device__ __forceinline__ void bulk_load(uint32_t dst, const void* src, uint32_t bytes, uint32_t bar) {
    asm volatile("cp.async.bulk.shared::cluster.global.mbarrier::complete_tx::bytes [%0], [%1], %2, [%3];"
        :: "r"(dst), "l"(src), "r"(bytes), "r"(bar) : "memory");
}
__device__ __forceinline__ void bulk_store(void* dst, uint32_t src, uint32_t bytes) {
    asm volatile("cp.async.bulk.global.shared::cta.bulk_group [%0], [%1], %2;" :: "l"(dst), "r"(src), "r"(bytes) : "memory");
}
__device__ __forceinline__ void tma2d_store(const CUtensorMap* tm, uint32_t src, int c0, int c1) {
    asm volatile("cp.async.bulk.tensor.2d.global.shared::cta.bulk_group [%0, {%2, %3}], [%1];" :: "l"(tm), "r"(src), "r"(c0), "r"(c1) : "memory");
}
__device__ __forceinline__ void cluster_sync_all() {
    asm volatile("barrier.cluster.arrive.relaxed;\nbarrier.cluster.wait;\n" ::: "memory");
}
__device__ __forceinline__ void wait_cnt(int idx, unsigned target) {
    const unsigned* p = &g_cnt[idx * 32];
    unsigned v;
    asm volatile("ld.relaxed.gpu.global.u32 %0, [%1];" : "=r"(v) : "l"(p) : "memory");
    if (v >= target) return;
    long long t0 = clock64();
    do {
        __nanosleep(40);
        asm volatile("ld.relaxed.gpu.global.u32 %0, [%1];" : "=r"(v) : "l"(p) : "memory");
        if (clock64() - t0 > 100000000LL) break;
    } while (v < target);
}
__device__ __forceinline__ void signal_cnt(int idx) {
    asm volatile("red.release.gpu.global.add.u32 [%0], 1;" :: "l"(&g_cnt[idx * 32]) : "memory");
}
__device__ __forceinline__ uint32_t pack2(float lo, float hi) {
    uint32_t r; asm("cvt.rn.bf16x2.f32 %0, %1, %2;" : "=r"(r) : "f"(hi), "f"(lo)); return r;
}
__device__ __forceinline__ float bf_lo(uint32_t v) { return __uint_as_float(v << 16); }
__device__ __forceinline__ float bf_hi(uint32_t v) { return __uint_as_float(v & 0xFFFF0000u); }
__device__ __forceinline__ float geglu(float g, float u) {
    float in = g * fmaf(g * g, 0.0356774081f, 0.7978845608f);
    float t; asm("tanh.approx.f32 %0, %1;" : "=f"(t) : "f"(in));
    float hg = 0.5f * g;
    return fmaf(hg, t, hg) * u;
}
__device__ __forceinline__ uint32_t lds32(uint32_t a) { uint32_t v; asm volatile("ld.shared.u32 %0, [%1];" : "=r"(v) : "r"(a)); return v; }
__device__ __forceinline__ float lds_bf(uint32_t a) { uint16_t v; asm volatile("ld.shared.u16 %0, [%1];" : "=h"(v) : "r"(a)); return __uint_as_float((uint32_t)v << 16); }
__device__ __forceinline__ float2 lds64f(uint32_t a) { float2 v; asm volatile("ld.shared.v2.f32 {%0,%1}, [%2];" : "=f"(v.x), "=f"(v.y) : "r"(a)); return v; }
__device__ __forceinline__ void sts64f(uint32_t a, float x, float y) { asm volatile("st.shared.v2.f32 [%0], {%1,%2};" :: "r"(a), "f"(x), "f"(y) : "memory"); }
__device__ __forceinline__ void stsm4_t(uint32_t a, uint32_t r0, uint32_t r1, uint32_t r2, uint32_t r3) {
    asm volatile("stmatrix.sync.aligned.m8n8.x4.trans.shared.b16 [%0], {%1,%2,%3,%4};" :: "r"(a), "r"(r0), "r"(r1), "r"(r2), "r"(r3) : "memory");
}
__device__ __forceinline__ void stsm4(uint32_t a, uint32_t r0, uint32_t r1, uint32_t r2, uint32_t r3) {
    asm volatile("stmatrix.sync.aligned.m8n8.x4.shared.b16 [%0], {%1,%2,%3,%4};" :: "r"(a), "r"(r0), "r"(r1), "r"(r2), "r"(r3) : "memory");
}
__device__ __forceinline__ void ldsm4(uint32_t a, uint32_t* r) {
    asm volatile("ldmatrix.sync.aligned.m8n8.x4.shared.b16 {%0,%1,%2,%3}, [%4];" : "=r"(r[0]), "=r"(r[1]), "=r"(r[2]), "=r"(r[3]) : "r"(a) : "memory");
}
__device__ __forceinline__ void ldsm4_t(uint32_t a, uint32_t* r) {
    asm volatile("ldmatrix.sync.aligned.m8n8.x4.trans.shared.b16 {%0,%1,%2,%3}, [%4];" : "=r"(r[0]), "=r"(r[1]), "=r"(r[2]), "=r"(r[3]) : "r"(a) : "memory");
}

struct Params {
    const bf16 *x, *k, *v, *shift_k, *ssm_k, *ssm_D, *gate_w;
};

template<int N, int SD> __device__ __forceinline__ void conv_group(float* acc, const uint32_t* a, uint64_t db0) {
    WG_FENCE();
    wgmma_rs<N, SD>(acc, a + 0, db0);
    wgmma_rs<N, 1>(acc, a + 4, db0 - 1);
    wgmma_rs<N, 1>(acc, a + 8, db0 - 4);
    wgmma_rs<N, 1>(acc, a + 12, db0 - 5);
    WG_COMMIT();
}
template<int NN> __device__ __forceinline__ void acc_redef(float* n, float* o) {
    #pragma unroll
    for (int j = 0; j < 8; j++) asm volatile("" : "+f"(o[j]) :: "memory");
    #pragma unroll
    for (int j = 0; j < NN; j++) asm volatile("add.f32 %0, %1, 0f00000000;" : "=f"(n[j]) : "f"(o[8 + j]) : "memory");
}
__device__ __forceinline__ void conv_loadA(uint32_t* a, uint32_t addr) {
    #pragma unroll
    for (int s = 0; s < 4; s++) {
        uint32_t o = addr + ((s & 1) + (s >> 1) * 4) * 32;
        a[4 * s + 0] = lds32(o);
        a[4 * s + 1] = lds32(o + 256);
        a[4 * s + 2] = lds32(o + 16);
        a[4 * s + 3] = lds32(o + 272);
    }
}
#define AFENCE(a) _Pragma("unroll") for (int _i = 0; _i < 16; _i++) asm volatile("" : "+r"(a[_i]) :: "memory")

__global__ void __cluster_dims__(2, 1, 1) __launch_bounds__(512, 1)
fused_kernel(const __grid_constant__ CUtensorMap tmX, const __grid_constant__ CUtensorMap tmWg, const __grid_constant__ CUtensorMap tmWu,
             const __grid_constant__ CUtensorMap tmH, const __grid_constant__ CUtensorMap tmWd, const __grid_constant__ CUtensorMap tmQ,
             const __grid_constant__ CUtensorMap tmZ, const __grid_constant__ CUtensorMap tmO,
             const Params prm) {
    extern __shared__ uint8_t smem_raw[];
    const uint32_t sb = ((uint32_t)__cvta_generic_to_shared(smem_raw) + 1023) & ~1023u;
    const uint32_t bars = sb + OFF_BAR;
    const int tid = threadIdx.x, wg = tid >> 7, warp = tid >> 5, lane = tid & 31;
    const int bid = blockIdx.x, rank = bid & 1, cl = bid >> 1;
    const int m1 = 2 * (cl & 7) + rank, role = cl >> 3;
    const int m2 = cl & 15, n2 = 2 * (cl >> 4) + rank;
    if (tid == 0) {
        for (int i = 0; i < NST1; i++) { mbar_init(bars + (B_FULL1 + i) * 8, 1); mbar_init(bars + (B_EMPTY1 + i) * 8, 4); }
        for (int i = 0; i < NST2; i++) { mbar_init(bars + (B_FULL2 + i) * 8, 1); mbar_init(bars + (B_EMPTY2 + i) * 8, 4); }
        for (int i = 0; i < 2; i++) { mbar_init(bars + (B_CFULL + i) * 8, 2); mbar_init(bars + (B_CDONE + i) * 8, 4); mbar_init(bars + (B_CRAW + i) * 8, 1); }
        mbar_init(bars + B_HD * 8, 8); mbar_init(bars + B_STG * 8, 1); mbar_init(bars + B_GO0 * 8, 2); mbar_init(bars + B_GO1 * 8, 2);
        asm volatile("fence.mbarrier_init.release.cluster;" ::: "memory");
    }
    if (wg == 3) {
        int t = tid - 384;
        if (t < 56) {
            int b = t / 28, j = t % 28;
            int off = j < 8 ? j * 16 : (j < 12 ? 4224 + (j - 8) * 16 : (j < 20 ? CB_P0 - 128 + (j - 12) * 16 : CB_P0 + CB_PS - 128 + (j - 20) * 16));
            asm volatile("st.shared.v4.u32 [%0], {%1,%1,%1,%1};" :: "r"(sb + OFF_CB + b * CB + off), "r"(0) : "memory");
        }
        FENCE_ASYNC_S();
    }
    __syncthreads();
    cluster_sync_all();

    if (wg == 0) {
        asm volatile("setmaxnreg.dec.sync.aligned.u32 40;\n");
        if (warp == 0 && lane == 0) {
            const CUtensorMap* tw = rank == 0 ? &tmWg : &tmWu;
            PROF(29);
            for (int it = 0; it < 20; it++) {
                int st = it & 3;
                mbar_wait(bars + (B_EMPTY1 + st) * 8, ((it >> 2) & 1) ^ 1);
                uint32_t full = bars + (B_FULL1 + st) * 8;
                mbar_expect_tx(full, ST1);
                int kb = it < 10 ? it : it - 10;
                int col = it < 10 ? role * 128 : 1024 + role * 96;
                uint32_t sa = sb + st * ST1, sw = sa + 16384 + rank * 16384;
                tma2d_mc(sw, tw, col, kb * 64, full);
                tma2d_mc(sw + 8192, tw, col + 64, kb * 64, full);
                tma2d(sa, &tmX, kb * 64, m1 * 128, full);
            }
            wait_cnt(C_H1 + m2, 8);
            FENCE_ASYNC_G();
            for (int st = 0; st < 4; st++) mbar_wait(bars + (B_EMPTY1 + st) * 8, 0);
            PROF(8);
            int st = 0; uint32_t ph = 1;
            for (int it = 0; it < 29; it++) {
                if (it == 16) { wait_cnt(C_H2 + m2, 8); FENCE_ASYNC_G(); PROF(9); }
                mbar_wait(bars + (B_EMPTY2 + st) * 8, ph);
                uint32_t full = bars + (B_FULL2 + st) * 8;
                uint32_t sa = sb + st * ST2;
                if (it < 27) {
                    mbar_expect_tx(full, ST2);
                    tma2d_mc(sa + rank * 8192, &tmH, it * 64, m2 * 128 + rank * 64, full);
                    tma5d(sa + 16384, &tmWd, it * 8, n2 * 5, full);
                } else if (it == 27) {
                    wait_cnt(C_G + m2, 8);
                    mbar_expect_tx(full, 20480);
                    tma2d(sa, &tmQ, n2 * 80, m2 * 128, full);
                } else {
                    PROF(10);
                    wait_cnt(C_Z + n2, 80);
                    FENCE_ASYNC_G();
                    PROF(11);
                    mbar_expect_tx(full, 20480);
                    tma2d(sa, &tmZ, m2 * 128, n2 * 80, full);
                    tma2d(sa + 10240, &tmZ, m2 * 128 + 64, n2 * 80, full);
                }
                if (++st == NST2) { st = 0; ph ^= 1; }
            }
            if (atomicAdd(&g_cnt[C_DONE * 32], 1u) == 127u) {
                for (int i = 0; i < C_NUM; i++) g_cnt[i * 32] = 0;
            }
        } else if (warp == 1 && lane == 0) {
            const int ch0 = bid * NCH;
            auto load_h = [&](int i) {
                uint32_t cb = sb + OFF_CB + (i & 1) * CB, full = bars + (B_CRAW + (i & 1)) * 8;
                mbar_expect_tx(full, 4096);
                bulk_load(cb + CB_HA, prm.ssm_k + (size_t)(ch0 + i) * SEQ, 4096, full);
            };
            auto load_x = [&](int i) {
                uint32_t cb = sb + OFF_CB + (i & 1) * CB, full = bars + (B_CFULL + (i & 1)) * 8;
                mbar_expect_tx(full, 4096);
                bulk_load(cb + CB_P0, g_kvT + (size_t)(ch0 + i) * SEQ, 2048, full);
                bulk_load(cb + CB_P0 + CB_PS, g_kvT + (size_t)(ch0 + i) * SEQ + 1024, 2048, full);
            };
            load_h(0); load_h(1);
            wait_cnt(C_KV + (bid >> 4), 16);
            FENCE_ASYNC_G();
            load_x(0); load_x(1);
            for (int i = 0; i < NCH; i++) {
                mbar_wait(bars + (B_CDONE + (i & 1)) * 8, (i >> 1) & 1);
                bulk_store(g_zT + (size_t)(ch0 + i) * SEQ, sb + OFF_STG, 4096);
                asm volatile("cp.async.bulk.commit_group;" ::: "memory");
                if (i + 2 < NCH) { load_h(i + 2); load_x(i + 2); }
                asm volatile("cp.async.bulk.wait_group.read 0;" ::: "memory");
                mbar_arrive(bars + B_STG * 8);
                asm volatile("cp.async.bulk.wait_group 0;" ::: "memory");
                FENCE_ASYNC_G();
                signal_cnt(C_Z + (bid >> 4));
            }
            PROF(12);
        } else if (warp == 2) {
            for (int i = 0; i < NCH; i++) {
                const uint32_t cb = sb + OFF_CB + (i & 1) * CB + lane * 16;
                mbar_wait(bars + (B_CRAW + (i & 1)) * 8, (i >> 1) & 1);
                #pragma unroll
                for (int j = 0; j < 8; j++) {
                    uint32_t x0, x1, x2, x3, pv = lds32(cb + CB_HA + j * 512 - 4);
                    asm volatile("ld.shared.v4.u32 {%0,%1,%2,%3}, [%4];" : "=r"(x0), "=r"(x1), "=r"(x2), "=r"(x3) : "r"(cb + CB_HA + j * 512));
                    asm volatile("st.shared.v4.u32 [%0], {%1,%2,%3,%4};" :: "r"(cb + CB_HB + j * 512), "r"(__byte_perm(pv, x0, 0x5432)), "r"(__byte_perm(x0, x1, 0x5432)),
                                 "r"(__byte_perm(x1, x2, 0x5432)), "r"(__byte_perm(x2, x3, 0x5432)) : "memory");
                }
                __syncwarp();
                if (lane == 0) mbar_arrive(bars + (B_CFULL + (i & 1)) * 8);
            }
        } else if (warp == 3 && lane == 0) {
            mbar_wait(bars + B_HD * 8, 0);
            signal_cnt(C_H1 + m1);
            mbar_wait(bars + B_HD * 8, 1);
            signal_cnt(C_H2 + m1);
        }
        __syncwarp();
        cluster_sync_all();
        if (tid == 0) { PROF(13); }
    } else if (wg == 3) {
        asm volatile("setmaxnreg.inc.sync.aligned.u32 136;\n");
        const int t = tid - 384, w = warp & 3;
        if (t == 0) { PROF(22); }
        const float Dall = lane < NCH ? __bfloat162float(prm.ssm_D[bid * NCH + lane]) : 0.f;
        for (int idx = t; idx < 160; idx += 128) {
            int cq = idx % 20, tg = idx / 20;
            int ch = role * 80 + cq * 4, t0 = m1 * 128 + tg * 16;
            uint2 kk[19], vv[16];
            #pragma unroll
            for (int j = 0; j < 19; j++) {
                int tt = t0 - 3 + j;
                kk[j] = tt >= 0 ? __ldg((const uint2*)(prm.k + (size_t)tt * DM + ch)) : make_uint2(0, 0);
            }
            #pragma unroll
            for (int j = 0; j < 16; j++) vv[j] = __ldg((const uint2*)(prm.v + (size_t)(t0 + j) * DM + ch));
            uint4 s0 = __ldg((const uint4*)(prm.shift_k + ch * 4)), s1 = __ldg((const uint4*)(prm.shift_k + ch * 4 + 8));
            #pragma unroll
            for (int c = 0; c < 4; c++) {
                uint32_t sa = c == 0 ? s0.x : c == 1 ? s0.z : c == 2 ? s1.x : s1.z;
                uint32_t sc = c == 0 ? s0.y : c == 1 ? s0.w : c == 2 ? s1.y : s1.w;
                float w0 = bf_lo(sa), w1 = bf_hi(sa), w2 = bf_lo(sc), w3 = bf_hi(sc);
                float kf[19];
                #pragma unroll
                for (int j = 0; j < 19; j++) { uint32_t u = c < 2 ? kk[j].x : kk[j].y; kf[j] = (c & 1) ? bf_hi(u) : bf_lo(u); }
                float r[16];
                #pragma unroll
                for (int j = 0; j < 16; j++) {
                    uint32_t u = c < 2 ? vv[j].x : vv[j].y; float vf = (c & 1) ? bf_hi(u) : bf_lo(u);
                    r[j] = (kf[j + 3] * w0 + kf[j + 2] * w1 + kf[j + 1] * w2 + kf[j] * w3) * vf;
                }
                bf16* dst = g_kvT + (size_t)(ch + c) * SEQ + (t0 >> 4) * 8;
                *(uint4*)dst = make_uint4(pack2(r[15], r[14]), pack2(r[13], r[12]), pack2(r[11], r[10]), pack2(r[9], r[8]));
                *(uint4*)(dst + 1024) = make_uint4(pack2(r[7], r[6]), pack2(r[5], r[4]), pack2(r[3], r[2]), pack2(r[1], r[0]));
            }
        }
        if (t == 0) { PROF(23); }
        if (t == 32) { PROF(24); }
        {
            int row0 = m1 * 128 + role * 16 + w * 4;
            uint4 gw[3], xx[4][3];
            #pragma unroll
            for (int j = 0; j < 3; j++) {
                bool ok = j < 2 || lane < 16;
                gw[j] = ok ? __ldg((const uint4*)(prm.gate_w + (j * 32 + lane) * 8)) : make_uint4(0, 0, 0, 0);
                #pragma unroll
                for (int r = 0; r < 4; r++) xx[r][j] = ok ? __ldg((const uint4*)(prm.x + (size_t)(row0 + r) * DM + (j * 32 + lane) * 8)) : make_uint4(0, 0, 0, 0);
            }
            #pragma unroll
            for (int r = 0; r < 4; r++) {
                float s = 0.f;
                #pragma unroll
                for (int j = 0; j < 3; j++) {
                    s += bf_lo(xx[r][j].x) * bf_lo(gw[j].x) + bf_hi(xx[r][j].x) * bf_hi(gw[j].x);
                    s += bf_lo(xx[r][j].y) * bf_lo(gw[j].y) + bf_hi(xx[r][j].y) * bf_hi(gw[j].y);
                    s += bf_lo(xx[r][j].z) * bf_lo(gw[j].z) + bf_hi(xx[r][j].z) * bf_hi(gw[j].z);
                    s += bf_lo(xx[r][j].w) * bf_lo(gw[j].w) + bf_hi(xx[r][j].w) * bf_hi(gw[j].w);
                }
                #pragma unroll
                for (int o = 16; o > 0; o >>= 1) s += __shfl_xor_sync(0xffffffffu, s, o);
                if (lane == 0) g_gate[row0 + r] = 1.0f / (1.0f + __expf(-s));
            }
        }
        if (t == 0) { PROF(25); }
        asm volatile("bar.sync 1, 128;" ::: "memory");
        if (t == 0) { __threadfence(); atomicAdd(&g_cnt[(C_KV + role) * 32], 1u); atomicAdd(&g_cnt[(C_G + m1) * 32], 1u); }
        if (t == 0) { PROF(14); }
        const int w0 = w & 1, w1 = w >> 1, r = lane >> 2, c = lane & 3;
        const uint32_t a_off = (r & 1) ? CB_HA + 2 * (32 * w1 + 8 * w0 + r - 15 + 2 * c) : CB_HB + 2 * (32 * w1 + 8 * w0 + r - 14 + 2 * c);
        const uint32_t stg = sb + OFF_STG;
        for (int i = 0; i < NCH; i++) {
            const uint32_t cb = sb + OFF_CB + (i & 1) * CB;
            const float Dv = __shfl_sync(0xffffffffu, Dall, i);
            if (i == GATE0) mbar_wait(bars + B_GO0 * 8, 0);
            if (i == GATE1) mbar_wait(bars + B_GO1 * 8, 0);
            mbar_wait(bars + (B_CFULL + (i & 1)) * 8, (i >> 1) & 1);
            if (t == 0) { PROF(16 + i); }
            float hi64[32], hi48[24], hi32[16], hi16[8], lo64[32], lo48[24], lo32[16], lo16[8];
            uint32_t a0[16], a1[16];
            const uint64_t db0 = make_desc(cb + CB_P0, CB_PS, 128, 0);
            const uint32_t aa = cb + a_off;
            conv_loadA(a0, aa);
            conv_loadA(a1, aa + 512);
            conv_group<64, 0>(hi64, a0, db0 + 64);
            conv_group<64, 1>(hi64, a1, db0 + 48);
            WG_WAIT(1); AFENCE(a0); conv_loadA(a0, aa + 2 * 512); conv_group<64, 1>(hi64, a0, db0 + 32);
            WG_WAIT(1); AFENCE(a1); conv_loadA(a1, aa + 3 * 512); conv_group<64, 1>(hi64, a1, db0 + 16);
            WG_WAIT(1); AFENCE(a0); conv_loadA(a0, aa + 4 * 512); conv_group<64, 1>(hi64, a0, db0);
            WG_WAIT(1); AFENCE(a1); conv_loadA(a1, aa + 0 * 512); conv_group<64, 0>(lo64, a1, db0);
            WG_WAIT(1); AFENCE(a0); conv_loadA(a0, aa + 5 * 512); acc_redef<24>(hi48, hi64); conv_group<48, 1>(hi48, a0, db0);
            WG_WAIT(1); AFENCE(a1); conv_loadA(a1, aa + 1 * 512); acc_redef<24>(lo48, lo64); conv_group<48, 1>(lo48, a1, db0);
            WG_WAIT(1); AFENCE(a0); conv_loadA(a0, aa + 6 * 512); acc_redef<16>(hi32, hi48); conv_group<32, 1>(hi32, a0, db0);
            WG_WAIT(1); AFENCE(a1); conv_loadA(a1, aa + 2 * 512); acc_redef<16>(lo32, lo48); conv_group<32, 1>(lo32, a1, db0);
            WG_WAIT(1); AFENCE(a0); conv_loadA(a0, aa + 7 * 512); acc_redef<8>(hi16, hi32); conv_group<16, 1>(hi16, a0, db0);
            WG_WAIT(1); AFENCE(a1); conv_loadA(a1, aa + 3 * 512); acc_redef<8>(lo16, lo32); conv_group<16, 1>(lo16, a1, db0);
            WG_WAIT(0);
            AFENCE(a0); AFENCE(a1);
            acc_redef<0>(nullptr, hi16); acc_redef<0>(nullptr, lo16);
            if (t == 0 && i == 3) { PROF(26); }
            float acc[64];
            #pragma unroll
            for (int j = 0; j < 8; j++) {
                acc[j] = lo64[j]; acc[8 + j] = lo48[j]; acc[16 + j] = lo32[j]; acc[24 + j] = lo16[j];
                acc[32 + j] = hi64[j]; acc[40 + j] = hi48[j]; acc[48 + j] = hi32[j]; acc[56 + j] = hi16[j];
            }
            #pragma unroll
            for (int q = 15; q >= 1; q--) { acc[4 * q] += acc[4 * q - 2]; acc[4 * q + 1] += acc[4 * q - 1]; }
            asm volatile("bar.sync 1, 128;" ::: "memory");
            const uint32_t xs1 = cb + CB_HA + w0 * 2048, xs0 = cb + CB_HB + w0 * 2048;
            if (w1 == 0) {
                #pragma unroll
                for (int q = 8; q < 16; q++) sts64f(xs0 + (q - 8) * 256 + lane * 8, acc[4 * q], acc[4 * q + 1]);
            } else {
                #pragma unroll
                for (int q = 0; q < 8; q++) sts64f(xs1 + q * 256 + lane * 8, acc[4 * q], acc[4 * q + 1]);
            }
            if (i > 0) mbar_wait(bars + B_STG * 8, (i - 1) & 1);
            asm volatile("bar.sync 1, 128;" ::: "memory");
            if (t == 0 && i == 3) { PROF(27); }
            const uint32_t kvp = cb + CB_P0 + (1 - w0) * CB_PS + (7 - r) * 2 + c * 32;
            uint32_t pk[8];
            if (w1 == 0) {
                const uint32_t rd = xs1 + (c > 0 ? lane * 8 - 8 : lane * 8 + 24 - 256);
                #pragma unroll
                for (int q = 0; q < 9; q++) {
                    float2 o = make_float2(0.f, 0.f);
                    if (q == 0) { if (c > 0) o = lds64f(rd); }
                    else if (q == 8) { if (c == 0) o = lds64f(rd + q * 256); }
                    else o = lds64f(rd + q * 256);
                    float z0 = fmaf(Dv, lds_bf(kvp + q * 128), acc[4 * q] + o.x);
                    float z1 = fmaf(Dv, lds_bf(kvp + q * 128 + 16), acc[4 * q + 1] + o.y);
                    uint32_t pz = pack2(z0, z1);
                    if (q < 8) pk[q] = pz;
                    else if (c == 0) {
                        asm volatile("st.shared.u16 [%0], %1;" :: "r"(stg + 64 * 32 + w0 * 16 + r * 2), "h"((uint16_t)(pz & 0xFFFF)) : "memory");
                        asm volatile("st.shared.u16 [%0], %1;" :: "r"(stg + 65 * 32 + w0 * 16 + r * 2), "h"((uint16_t)(pz >> 16)) : "memory");
                    }
                }
                stsm4_t(stg + lane * 32 + w0 * 16, pk[0], pk[1], pk[2], pk[3]);
                stsm4_t(stg + (32 + lane) * 32 + w0 * 16, pk[4], pk[5], pk[6], pk[7]);
            } else {
                const uint32_t rd = xs0 + (c < 3 ? lane * 8 + 8 : lane * 8 - 24 + 256);
                #pragma unroll
                for (int q = 8; q < 16; q++) {
                    float2 o = make_float2(0.f, 0.f);
                    float k0 = 0.f, k1 = 0.f;
                    if (q < 15 || c < 3) { o = lds64f(rd + (q - 8) * 256); k0 = lds_bf(kvp + q * 128 + 32); k1 = lds_bf(kvp + q * 128 + 48); }
                    pk[q - 8] = pack2(fmaf(Dv, k0, acc[4 * q] + o.x), fmaf(Dv, k1, acc[4 * q + 1] + o.y));
                }
                stsm4_t(stg + (66 + lane) * 32 + w0 * 16, pk[0], pk[1], pk[2], pk[3]);
                stsm4_t(stg + (98 + lane) * 32 + w0 * 16, pk[4], pk[5], pk[6], pk[7]);
            }
            FENCE_ASYNC_S();
            __syncwarp();
            if (lane == 0) mbar_arrive(bars + (B_CDONE + (i & 1)) * 8);
            if (t == 0 && i == 3) { PROF(28); }
        }
        if (t == 0) { PROF(21); }
        cluster_sync_all();
    } else {
        asm volatile("setmaxnreg.inc.sync.aligned.u32 168;\n");
        const int cw = wg - 1, t = tid & 127, w = warp & 3, r = lane >> 2, c = lane & 3;
        {
            float d[128];
            for (int it = 0; it < 10; it++) {
                int st = it & 3;
                mbar_wait(bars + (B_FULL1 + st) * 8, (it >> 2) & 1);
                if (it == 0 && tid == 128) { PROF(0); }
                uint64_t da = make_desc(sb + st * ST1 + cw * 8192, 16, 1024, 1);
                uint64_t db = make_desc(sb + st * ST1 + 16384, 8192, 1024, 1);
                WG_FENCE();
                #pragma unroll
                for (int k = 0; k < 4; k++) {
                    wgmma_ss_n128(d, da + k * 2, db + k * 128, (it | k) != 0);
                    wgmma_ss_n128(d + 64, da + k * 2, db + 1024 + k * 128, (it | k) != 0);
                }
                WG_COMMIT();
                WG_WAIT(1);
                if (it > 0 && t < 2) mbar_arrive_cluster(bars + (B_EMPTY1 + ((it - 1) & 3)) * 8, t);
            }
            WG_WAIT(0);
            #pragma unroll
            for (int j = 0; j < 128; j++) asm volatile("" : "+f"(d[j]) :: "memory");
            if (t < 2) mbar_arrive_cluster(bars + (B_EMPTY1 + 1) * 8, t);
            if (t == 2) mbar_arrive(bars + B_GO0 * 8);
            if (tid == 128) { PROF(1); }
            bf16* hrow = g_h + (size_t)(m1 * 128 + cw * 64 + w * 16 + r) * DF + c * 16;
            #pragma unroll
            for (int G = 0; G < 4; G++) {
                #pragma unroll
                for (int hf = 0; hf < 2; hf++) {
                    uint32_t p[4];
                    #pragma unroll
                    for (int q = 0; q < 4; q++) {
                        int j = (G * 4 + q) * 4 + hf * 2;
                        p[q] = pack2(geglu(d[j], d[64 + j]), geglu(d[j + 1], d[64 + j + 1]));
                    }
                    *(uint4*)(hrow + hf * 8 * DF + role * 128 + (G >> 1) * 64 + (G & 1) * 8) = make_uint4(p[0], p[1], p[2], p[3]);
                }
            }
            __syncwarp();
            if (lane == 0) mbar_arrive(bars + B_HD * 8);
            if (tid == 128) { PROF(2); }
            float d2[96];
            for (int it = 10; it < 20; it++) {
                int st = it & 3;
                mbar_wait(bars + (B_FULL1 + st) * 8, (it >> 2) & 1);
                uint64_t da = make_desc(sb + st * ST1 + cw * 8192, 16, 1024, 1);
                uint64_t db = make_desc(sb + st * ST1 + 16384, 8192, 1024, 1);
                WG_FENCE();
                #pragma unroll
                for (int k = 0; k < 4; k++) {
                    wgmma_ss_n96(d2, da + k * 2, db + k * 128, ((it - 10) | k) != 0);
                    wgmma_ss_n96(d2 + 48, da + k * 2, db + 1024 + k * 128, ((it - 10) | k) != 0);
                }
                WG_COMMIT();
                WG_WAIT(1);
                if (it > 10 && t < 2) mbar_arrive_cluster(bars + (B_EMPTY1 + ((it - 1) & 3)) * 8, t);
            }
            WG_WAIT(0);
            #pragma unroll
            for (int j = 0; j < 96; j++) asm volatile("" : "+f"(d2[j]) :: "memory");
            if (t < 2) mbar_arrive_cluster(bars + (B_EMPTY1 + 3) * 8, t);
            if (t == 2) mbar_arrive(bars + B_GO1 * 8);
            if (tid == 128) { PROF(3); }
            #pragma unroll
            for (int G = 0; G < 3; G++) {
                int Gg = 32 + role * 3 + G;
                if (Gg < DF / 32) {
                    #pragma unroll
                    for (int hf = 0; hf < 2; hf++) {
                        uint32_t p[4];
                        #pragma unroll
                        for (int q = 0; q < 4; q++) {
                            int j = (G * 4 + q) * 4 + hf * 2;
                            p[q] = pack2(geglu(d2[j], d2[48 + j]), geglu(d2[j + 1], d2[48 + j + 1]));
                        }
                        *(uint4*)(hrow + hf * 8 * DF + (Gg >> 1) * 64 + (Gg & 1) * 8) = make_uint4(p[0], p[1], p[2], p[3]);
                    }
                }
            }
            __syncwarp();
            if (lane == 0) mbar_arrive(bars + B_HD * 8);
            if (tid == 128) { PROF(4); }
        }
        float e[40];
        int st = 0, pst = 0; uint32_t ph = 0;
        for (int it = 0; it < 27; it++) {
            mbar_wait(bars + (B_FULL2 + st) * 8, ph);
            uint64_t da = make_desc(sb + st * ST2 + cw * 8192, 16, 1024, 1);
            uint64_t db = make_desc(sb + st * ST2 + 16384, 2048, 256, 3);
            WG_FENCE();
            #pragma unroll
            for (int k = 0; k < 4; k++) wgmma_ss_n80(e, da + k * 2, db + k * 32, (it | k) != 0);
            WG_COMMIT();
            WG_WAIT(1);
            if (it > 0 && t < 2) mbar_arrive_cluster(bars + (B_EMPTY2 + pst) * 8, t);
            pst = st;
            if (++st == NST2) { st = 0; ph ^= 1; }
        }
        WG_WAIT(0);
        #pragma unroll
        for (int j = 0; j < 40; j++) asm volatile("" : "+f"(e[j]) :: "memory");
        if (tid == 128) { PROF(5); }
        mbar_wait(bars + (B_FULL2 + 6) * 8, 1);
        const int row = m2 * 128 + cw * 64 + w * 16 + r;
        float g0 = __ldcg(&g_gate[row]), g1 = __ldcg(&g_gate[row + 8]);
        mbar_wait(bars + (B_FULL2 + 0) * 8, 0);
        if (tid == 128) { PROF(6); }
        const int mi = lane >> 3, l8 = lane & 7;
        const uint32_t qa = sb + 6 * ST2 + (cw * 64 + w * 16 + (mi & 1) * 8 + l8) * 160 + (mi >> 1) * 16;
        const uint32_t za = sb + cw * 10240 + ((mi >> 1) * 8 + l8) * 128 + (((2 * w + (mi & 1)) ^ l8) << 4);
        #pragma unroll
        for (int j = 0; j < 10; j += 2) {
            uint32_t qv[4], zv[4], o[4];
            ldsm4(qa + j * 16, qv);
            ldsm4_t(za + j * 1024, zv);
            #pragma unroll
            for (int u = 0; u < 4; u++) {
                float g = (u & 1) ? g1 : g0;
                int ei = (j + (u >> 1)) * 4 + (u & 1) * 2;
                float b0 = e[ei], b1 = e[ei + 1];
                float a0 = bf_lo(qv[u]) * bf_lo(zv[u]), a1 = bf_hi(qv[u]) * bf_hi(zv[u]);
                o[u] = pack2(fmaf(g, a0 - b0, b0), fmaf(g, a1 - b1, b1));
            }
            stsm4(qa + j * 16, o[0], o[1], o[2], o[3]);
        }
        FENCE_ASYNC_S();
        __syncwarp();
        if (lane == 0) {
            tma2d_store(&tmO, sb + 6 * ST2 + (cw * 64 + w * 16) * 160, n2 * 80, m2 * 128 + cw * 64 + w * 16);
            asm volatile("cp.async.bulk.commit_group;" ::: "memory");
            asm volatile("cp.async.bulk.wait_group.read 0;" ::: "memory");
        }
        if (tid == 128) { PROF(7); }
        __syncwarp();
        cluster_sync_all();
    }
}

#define CHK(x) (x)
typedef CUresult (*EncodeFn)(CUtensorMap*, CUtensorMapDataType, cuuint32_t, void*, const cuuint64_t*, const cuuint64_t*, const cuuint32_t*, const cuuint32_t*,
                             CUtensorMapInterleave, CUtensorMapSwizzle, CUtensorMapL2promotion, CUtensorMapFloatOOBfill);
static void mk2d(EncodeFn enc, CUtensorMap* m, const void* p, uint64_t d0, uint64_t d1, uint32_t b0, uint32_t b1, CUtensorMapSwizzle sw) {
    cuuint64_t gd[2] = {d0, d1}; cuuint64_t gs[1] = {d0 * 2}; cuuint32_t bd[2] = {b0, b1}; cuuint32_t es[2] = {1, 1};
    CHK(enc(m, CU_TENSOR_MAP_DATA_TYPE_BFLOAT16, 2, (void*)p, gd, gs, bd, es, CU_TENSOR_MAP_INTERLEAVE_NONE, sw, CU_TENSOR_MAP_L2_PROMOTION_L2_256B, CU_TENSOR_MAP_FLOAT_OOB_FILL_NONE));
}

extern "C" void kernel_launch(void* const* d_in, const int* in_sizes, int n_in, void* d_out, int out_size) {
    static EncodeFn enc = nullptr;
    static void *p_h = nullptr, *p_z = nullptr;
    if (!enc) {
        void* fn = nullptr; cudaDriverEntryPointQueryResult qr;
        cudaGetDriverEntryPoint("cuTensorMapEncodeTiled", &fn, cudaEnableDefault, &qr);
        enc = (EncodeFn)fn;
        cudaGetSymbolAddress(&p_h, g_h);
        cudaGetSymbolAddress(&p_z, g_zT);
        cudaFuncSetAttribute(fused_kernel, cudaFuncAttributeMaxDynamicSharedMemorySize, SMEM_TOTAL);
    }
    CUtensorMap tX, tWg, tWu, tH, tWd, tQ, tZ, tO;
    mk2d(enc, &tX, d_in[0], DM, SEQ, 64, 128, CU_TENSOR_MAP_SWIZZLE_128B);
    mk2d(enc, &tWg, d_in[7], DF, DM, 64, 64, CU_TENSOR_MAP_SWIZZLE_128B);
    mk2d(enc, &tWu, d_in[8], DF, DM, 64, 64, CU_TENSOR_MAP_SWIZZLE_128B);
    mk2d(enc, &tH, p_h, DF, SEQ, 64, 64, CU_TENSOR_MAP_SWIZZLE_128B);
    mk2d(enc, &tQ, d_in[0], DM, SEQ, 80, 128, CU_TENSOR_MAP_SWIZZLE_NONE);
    mk2d(enc, &tZ, p_z, SEQ, DM, 64, 80, CU_TENSOR_MAP_SWIZZLE_128B);
    mk2d(enc, &tO, d_out, DM, SEQ, 80, 16, CU_TENSOR_MAP_SWIZZLE_NONE);
    {
        cuuint64_t gd[5] = {16, 2, 216, 4, 40}; cuuint64_t gs[4] = {1280, 10240, 2560, 32};
        cuuint32_t bd[5] = {16, 2, 8, 4, 5}; cuuint32_t es[5] = {1, 1, 1, 1, 1};
        CHK(enc(&tWd, CU_TENSOR_MAP_DATA_TYPE_BFLOAT16, 5, d_in[9], gd, gs, bd, es, CU_TENSOR_MAP_INTERLEAVE_NONE, CU_TENSOR_MAP_SWIZZLE_32B,
            CU_TENSOR_MAP_L2_PROMOTION_L2_256B, CU_TENSOR_MAP_FLOAT_OOB_FILL_NONE));
    }
    Params prm;
    prm.x = (const bf16*)d_in[0]; prm.k = (const bf16*)d_in[1]; prm.v = (const bf16*)d_in[2]; prm.shift_k = (const bf16*)d_in[3];
    prm.ssm_k = (const bf16*)d_in[4]; prm.ssm_D = (const bf16*)d_in[5]; prm.gate_w = (const bf16*)d_in[10];
    fused_kernel<<<128, 512, SMEM_TOTAL>>>(tX, tWg, tWu, tH, tWd, tQ, tZ, tO, prm);
}
```

```cpp
#include <cuda_runtime.h>
#include <cuda.h>
#include <cuda_bf16.h>
#include <stdint.h>

typedef __nv_bfloat16 bf16;
constexpr int SEQ = 2048, DM = 640, DF = 1728;

__device__ __align__(1024) bf16 g_h[SEQ * DF];
__device__ __align__(1024) bf16 g_kvT[DM * SEQ];
__device__ __align__(1024) bf16 g_zT[DM * SEQ];
__device__ __align__(1024) bf16 g_wd[DF * DM];
__device__ float g_gate[SEQ];
constexpr int C_KV = 0, C_KV0 = 8, C_H1 = 24, C_H2 = 40, C_Z = 56, C_DONE = 64, C_W = 65, C_NUM = 66;
__device__ unsigned g_cnt[C_NUM * 32];
#define PROF(i)

constexpr int ST1 = 49152, NST1 = 4;
constexpr int ST2 = 36864, NST2 = 5, OFF_Q = 4 * ST2, OFF_Z = OFF_Q + 20480;
constexpr int RING = ST1 * NST1;
constexpr int CB_HB = 128, CB_HA = 4288, CB_P0 = 8576, CB_PS = 2176, CB = 12800;
constexpr int OFF_CB = RING;
constexpr int OFF_STG = OFF_CB + 2 * CB;
constexpr int OFF_KT = OFF_CB + CB, OFF_SK = OFF_STG + 4224 + 3968;
constexpr int OFF_BAR = OFF_SK + 640;
constexpr int SMEM_TOTAL = OFF_BAR + 384 + 1024;
constexpr int B_FULL1 = 0, B_EMPTY1 = 4, B_FULL2 = 8, B_EMPTY2 = 15, B_CFULL = 22, B_CDONE = 24, B_STG = 26, B_KV = 27, B_G = 28, B_CRAW = 29, B_HD = 31, B_WD = 32, B_KIN = 33, B_PRE = 34, B_QF = 13, B_ZF = 14, B_XFREE = 20, B_XF = 35, B_KV1 = 21;
#define CI 3
constexpr int NCH = 5;

#define KV_WAIT 0
__device__ __forceinline__ void wgmma_ss_n128(float* d, uint64_t da, uint64_t db, int sd) {
    asm volatile("{\n.reg .pred p;\nsetp.ne.b32 p, %66, 0;\nwgmma.mma_async.sync.aligned.m64n128k16.f32.bf16.bf16 {%0,%1,%2,%3,%4,%5,%6,%7,%8,%9,%10,%11,%12,%13,%14,%15,%16,%17,%18,%19,%20,%21,%22,%23,%24,%25,%26,%27,%28,%29,%30,%31,%32,%33,%34,%35,%36,%37,%38,%39,%40,%41,%42,%43,%44,%45,%46,%47,%48,%49,%50,%51,%52,%53,%54,%55,%56,%57,%58,%59,%60,%61,%62,%63}, %64, %65, p, 1, 1, 0, 1;\n}\n"
    : "+f"(d[0]),"+f"(d[1]),"+f"(d[2]),"+f"(d[3]),"+f"(d[4]),"+f"(d[5]),"+f"(d[6]),"+f"(d[7]),"+f"(d[8]),"+f"(d[9]),"+f"(d[10]),"+f"(d[11]),"+f"(d[12]),"+f"(d[13]),"+f"(d[14]),"+f"(d[15]),"+f"(d[16]),"+f"(d[17]),"+f"(d[18]),"+f"(d[19]),"+f"(d[20]),"+f"(d[21]),"+f"(d[22]),"+f"(d[23]),"+f"(d[24]),"+f"(d[25]),"+f"(d[26]),"+f"(d[27]),"+f"(d[28]),"+f"(d[29]),"+f"(d[30]),"+f"(d[31]),"+f"(d[32]),"+f"(d[33]),"+f"(d[34]),"+f"(d[35]),"+f"(d[36]),"+f"(d[37]),"+f"(d[38]),"+f"(d[39]),"+f"(d[40]),"+f"(d[41]),"+f"(d[42]),"+f"(d[43]),"+f"(d[44]),"+f"(d[45]),"+f"(d[46]),"+f"(d[47]),"+f"(d[48]),"+f"(d[49]),"+f"(d[50]),"+f"(d[51]),"+f"(d[52]),"+f"(d[53]),"+f"(d[54]),"+f"(d[55]),"+f"(d[56]),"+f"(d[57]),"+f"(d[58]),"+f"(d[59]),"+f"(d[60]),"+f"(d[61]),"+f"(d[62]),"+f"(d[63]) : "l"(da), "l"(db), "r"(sd));
}
__device__ __forceinline__ void wgmma_ss_n192(float* d, uint64_t da, uint64_t db, int sd) {
    asm volatile("{\n.reg .pred p;\nsetp.ne.b32 p, %98, 0;\nwgmma.mma_async.sync.aligned.m64n192k16.f32.bf16.bf16 {%0,%1,%2,%3,%4,%5,%6,%7,%8,%9,%10,%11,%12,%13,%14,%15,%16,%17,%18,%19,%20,%21,%22,%23,%24,%25,%26,%27,%28,%29,%30,%31,%32,%33,%34,%35,%36,%37,%38,%39,%40,%41,%42,%43,%44,%45,%46,%47,%48,%49,%50,%51,%52,%53,%54,%55,%56,%57,%58,%59,%60,%61,%62,%63,%64,%65,%66,%67,%68,%69,%70,%71,%72,%73,%74,%75,%76,%77,%78,%79,%80,%81,%82,%83,%84,%85,%86,%87,%88,%89,%90,%91,%92,%93,%94,%95}, %96, %97, p, 1, 1, 0, 1;\n}\n"
    : "+f"(d[0]),"+f"(d[1]),"+f"(d[2]),"+f"(d[3]),"+f"(d[4]),"+f"(d[5]),"+f"(d[6]),"+f"(d[7]),"+f"(d[8]),"+f"(d[9]),"+f"(d[10]),"+f"(d[11]),"+f"(d[12]),"+f"(d[13]),"+f"(d[14]),"+f"(d[15]),"+f"(d[16]),"+f"(d[17]),"+f"(d[18]),"+f"(d[19]),"+f"(d[20]),"+f"(d[21]),"+f"(d[22]),"+f"(d[23]),"+f"(d[24]),"+f"(d[25]),"+f"(d[26]),"+f"(d[27]),"+f"(d[28]),"+f"(d[29]),"+f"(d[30]),"+f"(d[31]),"+f"(d[32]),"+f"(d[33]),"+f"(d[34]),"+f"(d[35]),"+f"(d[36]),"+f"(d[37]),"+f"(d[38]),"+f"(d[39]),"+f"(d[40]),"+f"(d[41]),"+f"(d[42]),"+f"(d[43]),"+f"(d[44]),"+f"(d[45]),"+f"(d[46]),"+f"(d[47]),"+f"(d[48]),"+f"(d[49]),"+f"(d[50]),"+f"(d[51]),"+f"(d[52]),"+f"(d[53]),"+f"(d[54]),"+f"(d[55]),"+f"(d[56]),"+f"(d[57]),"+f"(d[58]),"+f"(d[59]),"+f"(d[60]),"+f"(d[61]),"+f"(d[62]),"+f"(d[63]),"+f"(d[64]),"+f"(d[65]),"+f"(d[66]),"+f"(d[67]),"+f"(d[68]),"+f"(d[69]),"+f"(d[70]),"+f"(d[71]),"+f"(d[72]),"+f"(d[73]),"+f"(d[74]),"+f"(d[75]),"+f"(d[76]),"+f"(d[77]),"+f"(d[78]),"+f"(d[79]),"+f"(d[80]),"+f"(d[81]),"+f"(d[82]),"+f"(d[83]),"+f"(d[84]),"+f"(d[85]),"+f"(d[86]),"+f"(d[87]),"+f"(d[88]),"+f"(d[89]),"+f"(d[90]),"+f"(d[91]),"+f"(d[92]),"+f"(d[93]),"+f"(d[94]),"+f"(d[95]) : "l"(da), "l"(db), "r"(sd));
}
__device__ __forceinline__ void wgmma_ss_n160(float* d, uint64_t da, uint64_t db, int sd) {
    asm volatile("{\n.reg .pred p;\nsetp.ne.b32 p, %82, 0;\nwgmma.mma_async.sync.aligned.m64n160k16.f32.bf16.bf16 {%0,%1,%2,%3,%4,%5,%6,%7,%8,%9,%10,%11,%12,%13,%14,%15,%16,%17,%18,%19,%20,%21,%22,%23,%24,%25,%26,%27,%28,%29,%30,%31,%32,%33,%34,%35,%36,%37,%38,%39,%40,%41,%42,%43,%44,%45,%46,%47,%48,%49,%50,%51,%52,%53,%54,%55,%56,%57,%58,%59,%60,%61,%62,%63,%64,%65,%66,%67,%68,%69,%70,%71,%72,%73,%74,%75,%76,%77,%78,%79}, %80, %81, p, 1, 1, 0, 1;\n}\n"
    : "+f"(d[0]),"+f"(d[1]),"+f"(d[2]),"+f"(d[3]),"+f"(d[4]),"+f"(d[5]),"+f"(d[6]),"+f"(d[7]),"+f"(d[8]),"+f"(d[9]),"+f"(d[10]),"+f"(d[11]),"+f"(d[12]),"+f"(d[13]),"+f"(d[14]),"+f"(d[15]),"+f"(d[16]),"+f"(d[17]),"+f"(d[18]),"+f"(d[19]),"+f"(d[20]),"+f"(d[21]),"+f"(d[22]),"+f"(d[23]),"+f"(d[24]),"+f"(d[25]),"+f"(d[26]),"+f"(d[27]),"+f"(d[28]),"+f"(d[29]),"+f"(d[30]),"+f"(d[31]),"+f"(d[32]),"+f"(d[33]),"+f"(d[34]),"+f"(d[35]),"+f"(d[36]),"+f"(d[37]),"+f"(d[38]),"+f"(d[39]),"+f"(d[40]),"+f"(d[41]),"+f"(d[42]),"+f"(d[43]),"+f"(d[44]),"+f"(d[45]),"+f"(d[46]),"+f"(d[47]),"+f"(d[48]),"+f"(d[49]),"+f"(d[50]),"+f"(d[51]),"+f"(d[52]),"+f"(d[53]),"+f"(d[54]),"+f"(d[55]),"+f"(d[56]),"+f"(d[57]),"+f"(d[58]),"+f"(d[59]),"+f"(d[60]),"+f"(d[61]),"+f"(d[62]),"+f"(d[63]),"+f"(d[64]),"+f"(d[65]),"+f"(d[66]),"+f"(d[67]),"+f"(d[68]),"+f"(d[69]),"+f"(d[70]),"+f"(d[71]),"+f"(d[72]),"+f"(d[73]),"+f"(d[74]),"+f"(d[75]),"+f"(d[76]),"+f"(d[77]),"+f"(d[78]),"+f"(d[79]) : "l"(da), "l"(db), "r"(sd));
}
__device__ __forceinline__ void wgmma_ss_n80(float* d, uint64_t da, uint64_t db, int sd) {
    asm volatile("{\n.reg .pred p;\nsetp.ne.b32 p, %42, 0;\nwgmma.mma_async.sync.aligned.m64n80k16.f32.bf16.bf16 {%0,%1,%2,%3,%4,%5,%6,%7,%8,%9,%10,%11,%12,%13,%14,%15,%16,%17,%18,%19,%20,%21,%22,%23,%24,%25,%26,%27,%28,%29,%30,%31,%32,%33,%34,%35,%36,%37,%38,%39}, %40, %41, p, 1, 1, 0, 1;\n}\n"
    : "+f"(d[0]),"+f"(d[1]),"+f"(d[2]),"+f"(d[3]),"+f"(d[4]),"+f"(d[5]),"+f"(d[6]),"+f"(d[7]),"+f"(d[8]),"+f"(d[9]),"+f"(d[10]),"+f"(d[11]),"+f"(d[12]),"+f"(d[13]),"+f"(d[14]),"+f"(d[15]),"+f"(d[16]),"+f"(d[17]),"+f"(d[18]),"+f"(d[19]),"+f"(d[20]),"+f"(d[21]),"+f"(d[22]),"+f"(d[23]),"+f"(d[24]),"+f"(d[25]),"+f"(d[26]),"+f"(d[27]),"+f"(d[28]),"+f"(d[29]),"+f"(d[30]),"+f"(d[31]),"+f"(d[32]),"+f"(d[33]),"+f"(d[34]),"+f"(d[35]),"+f"(d[36]),"+f"(d[37]),"+f"(d[38]),"+f"(d[39]) : "l"(da), "l"(db), "r"(sd));
}
template<int SD> __device__ __forceinline__ void wgmma_rs_n16(float* d, const uint32_t* a, uint64_t db) {
    asm volatile("wgmma.mma_async.sync.aligned.m64n16k16.f32.bf16.bf16 {%0,%1,%2,%3,%4,%5,%6,%7}, {%8,%9,%10,%11}, %12, %13, 1, 1, 0;\n"
    : "+f"(d[0]),"+f"(d[1]),"+f"(d[2]),"+f"(d[3]),"+f"(d[4]),"+f"(d[5]),"+f"(d[6]),"+f"(d[7]) : "r"(a[0]), "r"(a[1]), "r"(a[2]), "r"(a[3]), "l"(db), "n"(SD));
}
template<int SD> __device__ __forceinline__ void wgmma_rs_n32(float* d, const uint32_t* a, uint64_t db) {
    asm volatile("wgmma.mma_async.sync.aligned.m64n32k16.f32.bf16.bf16 {%0,%1,%2,%3,%4,%5,%6,%7,%8,%9,%10,%11,%12,%13,%14,%15}, {%16,%17,%18,%19}, %20, %21, 1, 1, 0;\n"
    : "+f"(d[0]),"+f"(d[1]),"+f"(d[2]),"+f"(d[3]),"+f"(d[4]),"+f"(d[5]),"+f"(d[6]),"+f"(d[7]),"+f"(d[8]),"+f"(d[9]),"+f"(d[10]),"+f"(d[11]),"+f"(d[12]),"+f"(d[13]),"+f"(d[14]),"+f"(d[15]) : "r"(a[0]), "r"(a[1]), "r"(a[2]), "r"(a[3]), "l"(db), "n"(SD));
}
template<int SD> __device__ __forceinline__ void wgmma_rs_n48(float* d, const uint32_t* a, uint64_t db) {
    asm volatile("wgmma.mma_async.sync.aligned.m64n48k16.f32.bf16.bf16 {%0,%1,%2,%3,%4,%5,%6,%7,%8,%9,%10,%11,%12,%13,%14,%15,%16,%17,%18,%19,%20,%21,%22,%23}, {%24,%25,%26,%27}, %28, %29, 1, 1, 0;\n"
    : "+f"(d[0]),"+f"(d[1]),"+f"(d[2]),"+f"(d[3]),"+f"(d[4]),"+f"(d[5]),"+f"(d[6]),"+f"(d[7]),"+f"(d[8]),"+f"(d[9]),"+f"(d[10]),"+f"(d[11]),"+f"(d[12]),"+f"(d[13]),"+f"(d[14]),"+f"(d[15]),"+f"(d[16]),"+f"(d[17]),"+f"(d[18]),"+f"(d[19]),"+f"(d[20]),"+f"(d[21]),"+f"(d[22]),"+f"(d[23]) : "r"(a[0]), "r"(a[1]), "r"(a[2]), "r"(a[3]), "l"(db), "n"(SD));
}
template<int SD> __device__ __forceinline__ void wgmma_rs_n64(float* d, const uint32_t* a, uint64_t db) {
    asm volatile("wgmma.mma_async.sync.aligned.m64n64k16.f32.bf16.bf16 {%0,%1,%2,%3,%4,%5,%6,%7,%8,%9,%10,%11,%12,%13,%14,%15,%16,%17,%18,%19,%20,%21,%22,%23,%24,%25,%26,%27,%28,%29,%30,%31}, {%32,%33,%34,%35}, %36, %37, 1, 1, 0;\n"
    : "+f"(d[0]),"+f"(d[1]),"+f"(d[2]),"+f"(d[3]),"+f"(d[4]),"+f"(d[5]),"+f"(d[6]),"+f"(d[7]),"+f"(d[8]),"+f"(d[9]),"+f"(d[10]),"+f"(d[11]),"+f"(d[12]),"+f"(d[13]),"+f"(d[14]),"+f"(d[15]),"+f"(d[16]),"+f"(d[17]),"+f"(d[18]),"+f"(d[19]),"+f"(d[20]),"+f"(d[21]),"+f"(d[22]),"+f"(d[23]),"+f"(d[24]),"+f"(d[25]),"+f"(d[26]),"+f"(d[27]),"+f"(d[28]),"+f"(d[29]),"+f"(d[30]),"+f"(d[31]) : "r"(a[0]), "r"(a[1]), "r"(a[2]), "r"(a[3]), "l"(db), "n"(SD));
}
template<int SD> __device__ __forceinline__ void wgmma_rs_n128(float* d, const uint32_t* a, uint64_t db) {
    asm volatile("wgmma.mma_async.sync.aligned.m64n128k16.f32.bf16.bf16 {%0,%1,%2,%3,%4,%5,%6,%7,%8,%9,%10,%11,%12,%13,%14,%15,%16,%17,%18,%19,%20,%21,%22,%23,%24,%25,%26,%27,%28,%29,%30,%31,%32,%33,%34,%35,%36,%37,%38,%39,%40,%41,%42,%43,%44,%45,%46,%47,%48,%49,%50,%51,%52,%53,%54,%55,%56,%57,%58,%59,%60,%61,%62,%63}, {%64,%65,%66,%67}, %68, %69, 1, 1, 0;\n"
    : "+f"(d[0]),"+f"(d[1]),"+f"(d[2]),"+f"(d[3]),"+f"(d[4]),"+f"(d[5]),"+f"(d[6]),"+f"(d[7]),"+f"(d[8]),"+f"(d[9]),"+f"(d[10]),"+f"(d[11]),"+f"(d[12]),"+f"(d[13]),"+f"(d[14]),"+f"(d[15]),"+f"(d[16]),"+f"(d[17]),"+f"(d[18]),"+f"(d[19]),"+f"(d[20]),"+f"(d[21]),"+f"(d[22]),"+f"(d[23]),"+f"(d[24]),"+f"(d[25]),"+f"(d[26]),"+f"(d[27]),"+f"(d[28]),"+f"(d[29]),"+f"(d[30]),"+f"(d[31]),"+f"(d[32]),"+f"(d[33]),"+f"(d[34]),"+f"(d[35]),"+f"(d[36]),"+f"(d[37]),"+f"(d[38]),"+f"(d[39]),"+f"(d[40]),"+f"(d[41]),"+f"(d[42]),"+f"(d[43]),"+f"(d[44]),"+f"(d[45]),"+f"(d[46]),"+f"(d[47]),"+f"(d[48]),"+f"(d[49]),"+f"(d[50]),"+f"(d[51]),"+f"(d[52]),"+f"(d[53]),"+f"(d[54]),"+f"(d[55]),"+f"(d[56]),"+f"(d[57]),"+f"(d[58]),"+f"(d[59]),"+f"(d[60]),"+f"(d[61]),"+f"(d[62]),"+f"(d[63]) : "r"(a[0]), "r"(a[1]), "r"(a[2]), "r"(a[3]), "l"(db), "n"(SD));
}
template<int N, int SD> __device__ __forceinline__ void wgmma_rs(float* d, const uint32_t* a, uint64_t db) {
    if constexpr (N == 16) wgmma_rs_n16<SD>(d, a, db);
    if constexpr (N == 32) wgmma_rs_n32<SD>(d, a, db);
    if constexpr (N == 48) wgmma_rs_n48<SD>(d, a, db);
    if constexpr (N == 64) wgmma_rs_n64<SD>(d, a, db);
    if constexpr (N == 128) wgmma_rs_n128<SD>(d, a, db);
}

__device__ __forceinline__ uint64_t make_desc(uint32_t saddr, uint32_t lbo, uint32_t sbo, uint32_t swz) {
    uint64_t d = 0;
    d |= (uint64_t)((saddr & 0x3FFFF) >> 4);
    d |= (uint64_t)((lbo & 0x3FFFF) >> 4) << 16;
    d |= (uint64_t)((sbo & 0x3FFFF) >> 4) << 32;
    d |= (uint64_t)swz << 62;
    return d;
}
#define WG_FENCE() asm volatile("wgmma.fence.sync.aligned;\n" ::: "memory")
#define WG_COMMIT() asm volatile("wgmma.commit_group.sync.aligned;\n" ::: "memory")
#define WG_WAIT(n) asm volatile("wgmma.wait_group.sync.aligned %0;\n" :: "n"(n) : "memory")
#define PP_SYNC() asm volatile("bar.sync %0, 256;" :: "r"(2 + cw) : "memory")
#define PP_ARRIVE() asm volatile("bar.arrive %0, 256;" :: "r"(3 - cw) : "memory")
#define FENCE_ASYNC_S() asm volatile("fence.proxy.async.shared::cta;\n" ::: "memory")
#define FENCE_ASYNC_G() asm volatile("fence.proxy.async.global;\n" ::: "memory")

__device__ __forceinline__ void mbar_init(uint32_t bar, uint32_t cnt) { asm volatile("mbarrier.init.shared::cta.b64 [%0], %1;" :: "r"(bar), "r"(cnt)); }
__device__ __forceinline__ void mbar_expect_tx(uint32_t bar, uint32_t bytes) { asm volatile("mbarrier.arrive.expect_tx.shared::cta.b64 _, [%0], %1;" :: "r"(bar), "r"(bytes) : "memory"); }
__device__ __forceinline__ void mbar_arrive(uint32_t bar) { asm volatile("mbarrier.arrive.shared::cta.b64 _, [%0];" :: "r"(bar) : "memory"); }
__device__ __forceinline__ bool mbar_try(uint32_t bar, uint32_t parity) {
    uint32_t ok;
    asm volatile("{\n.reg .pred p;\nmbarrier.try_wait.parity.shared::cta.b64 p, [%1], %2;\nselp.u32 %0, 1, 0, p;\n}\n" : "=r"(ok) : "r"(bar), "r"(parity) : "memory");
    return ok != 0;
}
__device__ __forceinline__ void mbar_wait(uint32_t bar, uint32_t parity) {
    if (mbar_try(bar, parity)) return;
    if (mbar_try(bar, parity)) return;
    long long t0 = clock64();
    while (!mbar_try(bar, parity)) { if (clock64() - t0 > 100000000LL) break; }
}
__device__ __forceinline__ void mbar_arrive_cluster(uint32_t bar, uint32_t cta) {
    asm volatile("{\n.reg .b32 ra;\nmapa.shared::cluster.u32 ra, %0, %1;\nmbarrier.arrive.shared::cluster.b64 _, [ra];\n}\n" :: "r"(bar), "r"(cta) : "memory");
}
__device__ __forceinline__ void tma2d(uint32_t dst, const CUtensorMap* tm, int c0, int c1, uint32_t bar) {
    asm volatile("cp.async.bulk.tensor.2d.shared::cluster.global.mbarrier::complete_tx::bytes [%0], [%1, {%3, %4}], [%2];"
        :: "r"(dst), "l"(tm), "r"(bar), "r"(c0), "r"(c1) : "memory");
}
__device__ __forceinline__ void tma2d_mc(uint32_t dst, const CUtensorMap* tm, int c0, int c1, uint32_t bar) {
    asm volatile("cp.async.bulk.tensor.2d.shared::cluster.global.mbarrier::complete_tx::bytes.multicast::cluster [%0], [%1, {%3, %4}], [%2], %5;"
        :: "r"(dst), "l"(tm), "r"(bar), "r"(c0), "r"(c1), "h"((uint16_t)3) : "memory");
}
__device__ __forceinline__ void bulk_load(uint32_t dst, const void* src, uint32_t bytes, uint32_t bar) {
    asm volatile("cp.async.bulk.shared::cluster.global.mbarrier::complete_tx::bytes [%0], [%1], %2, [%3];"
        :: "r"(dst), "l"(src), "r"(bytes), "r"(bar) : "memory");
}
__device__ __forceinline__ void tma3d_mc(uint32_t dst, const CUtensorMap* tm, int c1, int c2, uint32_t bar) {
    asm volatile("cp.async.bulk.tensor.3d.shared::cluster.global.mbarrier::complete_tx::bytes.multicast::cluster [%0], [%1, {%3, %4, %5}], [%2], %6;"
        :: "r"(dst), "l"(tm), "r"(bar), "r"(0), "r"(c1), "r"(c2), "h"((uint16_t)3) : "memory");
}
__device__ __forceinline__ void tma5d(uint32_t dst, const CUtensorMap* tm, int c0, int c4, uint32_t bar) {
    asm volatile("cp.async.bulk.tensor.5d.shared::cluster.global.mbarrier::complete_tx::bytes [%0], [%1, {%4, %3, %3, %3, %5}], [%2];"
        :: "r"(dst), "l"(tm), "r"(bar), "r"(0), "r"(c0), "r"(c4) : "memory");
}
__device__ __forceinline__ void l2_prefetch(const void* src, uint32_t bytes) {
    asm volatile("cp.async.bulk.prefetch.L2.global [%0], %1;" :: "l"(src), "r"(bytes) : "memory");
}
__device__ __forceinline__ void bulk_store(void* dst, uint32_t src, uint32_t bytes) {
    asm volatile("cp.async.bulk.global.shared::cta.bulk_group [%0], [%1], %2;" :: "l"(dst), "r"(src), "r"(bytes) : "memory");
}
__device__ __forceinline__ void tma2d_store(const CUtensorMap* tm, uint32_t src, int c0, int c1) {
    asm volatile("cp.async.bulk.tensor.2d.global.shared::cta.bulk_group [%0, {%2, %3}], [%1];" :: "l"(tm), "r"(src), "r"(c0), "r"(c1) : "memory");
}
__device__ __forceinline__ void cluster_sync_all() {
    asm volatile("barrier.cluster.arrive.relaxed;\nbarrier.cluster.wait;\n" ::: "memory");
}
__device__ __forceinline__ void wait_cnt(int idx, unsigned target) {
    const unsigned* p = &g_cnt[idx * 32];
    unsigned v;
    asm volatile("ld.relaxed.gpu.global.u32 %0, [%1];" : "=r"(v) : "l"(p) : "memory");
    if (v >= target) return;
    long long t0 = clock64();
    do {
        __nanosleep(40);
        asm volatile("ld.relaxed.gpu.global.u32 %0, [%1];" : "=r"(v) : "l"(p) : "memory");
        if (clock64() - t0 > 100000000LL) break;
    } while (v < target);
}
__device__ __forceinline__ void signal_cnt(int idx) {
    asm volatile("red.release.gpu.global.add.u32 [%0], 1;" :: "l"(&g_cnt[idx * 32]) : "memory");
}
__device__ __forceinline__ void signal_cnt_bulk(int idx) {
    asm volatile("red.relaxed.gpu.global.add.u32 [%0], 1;" :: "l"(&g_cnt[idx * 32]) : "memory");
}
__device__ __forceinline__ uint32_t pack2(float lo, float hi) {
    uint32_t r; asm("cvt.rn.bf16x2.f32 %0, %1, %2;" : "=r"(r) : "f"(hi), "f"(lo)); return r;
}
__device__ __forceinline__ uint32_t hmul2(uint32_t a, uint32_t b) { uint32_t r; asm("mul.rn.bf16x2 %0, %1, %2;" : "=r"(r) : "r"(a), "r"(b)); return r; }
__device__ __forceinline__ uint32_t hfma2(uint32_t a, uint32_t b, uint32_t c) { uint32_t r; asm("fma.rn.bf16x2 %0, %1, %2, %3;" : "=r"(r) : "r"(a), "r"(b), "r"(c)); return r; }
__device__ __forceinline__ float bf_lo(uint32_t v) { return __uint_as_float(v << 16); }
__device__ __forceinline__ float bf_hi(uint32_t v) { return __uint_as_float(v & 0xFFFF0000u); }
__device__ __forceinline__ float geglu(float g, float u) {
    float in = g * fmaf(g * g, 0.0356774081f, 0.7978845608f);
    float t; asm("tanh.approx.f32 %0, %1;" : "=f"(t) : "f"(in));
    float hg = 0.5f * g;
    return fmaf(hg, t, hg) * u;
}
__device__ __forceinline__ uint32_t lds32(uint32_t a) { uint32_t v; asm volatile("ld.shared.u32 %0, [%1];" : "=r"(v) : "r"(a)); return v; }
__device__ __forceinline__ float lds_bf(uint32_t a) { uint16_t v; asm volatile("ld.shared.u16 %0, [%1];" : "=h"(v) : "r"(a)); return __uint_as_float((uint32_t)v << 16); }
__device__ __forceinline__ float2 lds64f(uint32_t a) { float2 v; asm volatile("ld.shared.v2.f32 {%0,%1}, [%2];" : "=f"(v.x), "=f"(v.y) : "r"(a)); return v; }
__device__ __forceinline__ void sts64f(uint32_t a, float x, float y) { asm volatile("st.shared.v2.f32 [%0], {%1,%2};" :: "r"(a), "f"(x), "f"(y) : "memory"); }
__device__ __forceinline__ void stsm4_t(uint32_t a, uint32_t r0, uint32_t r1, uint32_t r2, uint32_t r3) {
    asm volatile("stmatrix.sync.aligned.m8n8.x4.trans.shared.b16 [%0], {%1,%2,%3,%4};" :: "r"(a), "r"(r0), "r"(r1), "r"(r2), "r"(r3) : "memory");
}
__device__ __forceinline__ void stsm4(uint32_t a, uint32_t r0, uint32_t r1, uint32_t r2, uint32_t r3) {
    asm volatile("stmatrix.sync.aligned.m8n8.x4.shared.b16 [%0], {%1,%2,%3,%4};" :: "r"(a), "r"(r0), "r"(r1), "r"(r2), "r"(r3) : "memory");
}
__device__ __forceinline__ void ldsm4(uint32_t a, uint32_t* r) {
    asm volatile("ldmatrix.sync.aligned.m8n8.x4.shared.b16 {%0,%1,%2,%3}, [%4];" : "=r"(r[0]), "=r"(r[1]), "=r"(r[2]), "=r"(r[3]) : "r"(a) : "memory");
}
__device__ __forceinline__ void ldsm4_t(uint32_t a, uint32_t* r) {
    asm volatile("ldmatrix.sync.aligned.m8n8.x4.trans.shared.b16 {%0,%1,%2,%3}, [%4];" : "=r"(r[0]), "=r"(r[1]), "=r"(r[2]), "=r"(r[3]) : "r"(a) : "memory");
}

__device__ __forceinline__ void zero_pad(uint32_t cb, int j) {
    int off = j < 8 ? j * 16 : (j < 12 ? 4224 + (j - 8) * 16 : (j < 20 ? CB_P0 - 128 + (j - 12) * 16 : CB_P0 + CB_PS - 128 + (j - 20) * 16));
    asm volatile("st.shared.v4.u32 [%0], {%1,%1,%1,%1};" :: "r"(cb + off), "r"(0) : "memory");
    FENCE_ASYNC_S();
}

struct Params {
    const bf16 *x, *k, *v, *shift_k, *ssm_k, *ssm_D, *gate_w, *wd, *wg, *wu;
};

template<int N, int SD> __device__ __forceinline__ void conv_group(float* acc, const uint32_t* a, uint64_t db0) {
    WG_FENCE();
    wgmma_rs<N, SD>(acc, a + 0, db0);
    wgmma_rs<N, 1>(acc, a + 4, db0 - 1);
    wgmma_rs<N, 1>(acc, a + 8, db0 - 4);
    wgmma_rs<N, 1>(acc, a + 12, db0 - 5);
    WG_COMMIT();
}
template<int NO> __device__ __forceinline__ void acc_widen(float* n, float* o) {
    #pragma unroll
    for (int j = 0; j < 8; j++) asm volatile("mov.b32 %0, 0;" : "=f"(n[j]) :: "memory");
    #pragma unroll
    for (int j = 0; j < NO; j++) asm volatile("add.f32 %0, %1, 0f00000000;" : "=f"(n[8 + j]) : "f"(o[j]) : "memory");
}
template<int N> __device__ __forceinline__ void acc_fence(float* o) {
    #pragma unroll
    for (int j = 0; j < N; j++) asm volatile("" : "+f"(o[j]) :: "memory");
}
__device__ __forceinline__ void conv_loadA(uint32_t* a, uint32_t addr) {
    #pragma unroll
    for (int s = 0; s < 4; s++) {
        uint32_t o = addr + ((s & 1) + (s >> 1) * 4) * 32;
        a[4 * s + 0] = lds32(o);
        a[4 * s + 1] = lds32(o + 256);
        a[4 * s + 2] = lds32(o + 16);
        a[4 * s + 3] = lds32(o + 272);
    }
}
#define AFENCE(a) _Pragma("unroll") for (int _i = 0; _i < 16; _i++) asm volatile("" : "+r"(a[_i]) :: "memory")

__global__ void __cluster_dims__(2, 1, 1) __launch_bounds__(512, 1)
fused_kernel(const __grid_constant__ CUtensorMap tmX, const __grid_constant__ CUtensorMap tmWg, const __grid_constant__ CUtensorMap tmWu,
             const __grid_constant__ CUtensorMap tmWg2, const __grid_constant__ CUtensorMap tmWu2, const __grid_constant__ CUtensorMap tmWd,
             const __grid_constant__ CUtensorMap tmK, const __grid_constant__ CUtensorMap tmQ,
             const __grid_constant__ CUtensorMap tmZ, const __grid_constant__ CUtensorMap tmO,
             const Params prm) {
    extern __shared__ uint8_t smem_raw[];
    const uint32_t sb = ((uint32_t)__cvta_generic_to_shared(smem_raw) + 1023) & ~1023u;
    const uint32_t bars = sb + OFF_BAR;
    const int tid = threadIdx.x, wg = tid >> 7, warp = tid >> 5, lane = tid & 31;
    const int bid = blockIdx.x, rank = bid & 1, cl = bid >> 1;
    const int m1 = 2 * (cl & 7) + rank, role = cl >> 3;
    const int m2 = cl & 15, n2 = 2 * (cl >> 4) + rank;
    if (tid == 0) {
        for (int i = 0; i < NST1; i++) { mbar_init(bars + (B_FULL1 + i) * 8, 1); mbar_init(bars + (B_EMPTY1 + i) * 8, 4); }
        for (int i = 0; i < NST2; i++) { mbar_init(bars + (B_FULL2 + i) * 8, 1); mbar_init(bars + (B_EMPTY2 + i) * 8, 2); }
        mbar_init(bars + B_QF * 8, 1); mbar_init(bars + B_ZF * 8, 1); mbar_init(bars + B_XFREE * 8, 2);
        for (int i = 0; i < 2; i++) { mbar_init(bars + (B_XF + i) * 8, 1); mbar_expect_tx(bars + (B_XF + i) * 8, 20480); }
        for (int i = 0; i < 2; i++) { mbar_init(bars + (B_CFULL + i) * 8, 2); mbar_init(bars + (B_CDONE + i) * 8, 4); mbar_init(bars + (B_CRAW + i) * 8, 1); }
        mbar_init(bars + B_HD * 8, 8); mbar_init(bars + B_WD * 8, 1); mbar_init(bars + B_KIN * 8, 1); mbar_init(bars + B_PRE * 8, 1); mbar_init(bars + B_STG * 8, 1); mbar_init(bars + B_KV * 8, 4); mbar_init(bars + B_KV1 * 8, 4); mbar_init(bars + B_G * 8, 4);
        asm volatile("fence.mbarrier_init.release.cluster;" ::: "memory");
    }
    if (tid >= 384 && tid < 412) zero_pad(sb + OFF_CB, tid - 384);
    __syncthreads();
    cluster_sync_all();

    if (wg == 0) {
        asm volatile("setmaxnreg.dec.sync.aligned.u32 40;\n");
        if (warp == 0 && lane == 0) {
            const CUtensorMap* tw = rank == 0 ? &tmWg : &tmWu;
            PROF(29);
            for (int it = 0; it < 20; it++) {
                int st = it & 3;
                mbar_wait(bars + (B_EMPTY1 + st) * 8, ((it >> 2) & 1) ^ 1);
                uint32_t full = bars + (B_FULL1 + st) * 8;
                uint32_t sa = sb + st * ST1;
                if (it < 10) {
                    mbar_expect_tx(full, ST1);
                    tma2d_mc(sa + 16384 + rank * 16384, tw, role * 128, it * 64, full);
                    tma2d_mc(sa + 24576 + rank * 16384, tw, role * 128 + 64, it * 64, full);
                    tma2d(sa, &tmX, it * 64, m1 * 128, full);
                } else {
                    int kb = it < 14 ? it - 4 : it - 14;
                    mbar_expect_tx(full, it < 14 ? 24576 : 40960);
                    tma3d_mc(sa + 16384 + rank * 12288, rank == 0 ? &tmWg2 : &tmWu2, kb * 64, 32 + 3 * role, full);
                    if (it >= 14) tma2d(sa, &tmX, kb * 64, m1 * 128, full);
                    if (it < 13 && bid < 120) {
                        if (it == 10) mbar_expect_tx(bars + B_WD * 8, 9 * 2048);
                        for (int q = 0; q < 3; q++) {
                            int pi = bid * 9 + (it - 10) * 3 + q, img = pi / 10, np = img / 27;
                            tma5d(sa + 40960 + q * 2048, &tmWd, np * 160 + (pi - img * 10) * 16, (img - np * 27) * 2, bars + B_WD * 8);
                        }
                    }
                }
            }
            wait_cnt(C_W, 120);
            wait_cnt(C_H1 + m2, 8);
            FENCE_ASYNC_G();
            PROF(8);
            int st = 0; uint32_t ph = 1;
            for (int it = 0; it < 14; it++) {
                if (it < 5) mbar_wait(bars + (B_EMPTY1 + (it < 3 ? it : it - 1)) * 8, 0);
                else mbar_wait(bars + (B_EMPTY2 + st) * 8, ph);
                uint32_t full = bars + (B_FULL2 + st) * 8;
                uint32_t sa = sb + st * ST2;
                int kb = it < 13 ? 2 * it + rank : 26;
                mbar_expect_tx(full, it < 13 ? ST2 : 26624);
                bulk_load(sa + 16384, g_wd + ((cl >> 4) * 27 + kb) * 10240 + (it < 13 ? 0 : rank * 5120), it < 13 ? 20480 : 10240, full);
                if (it == 8) { wait_cnt(C_H2 + m2, 8); FENCE_ASYNC_G(); PROF(9); }
                bulk_load(sa, g_h + (m2 * 27 + kb) * 8192, 16384, full);
                if (++st == NST2) { st = 0; ph ^= 1; }
            }
            mbar_wait(bars + (B_EMPTY2 + 4) * 8, 1);
            mbar_expect_tx(bars + B_QF * 8, 20480);
            tma2d(sb + OFF_Q, &tmQ, n2 * 80, m2 * 128, bars + B_QF * 8);
            PROF(10);
            wait_cnt(C_Z + n2, 80);
            FENCE_ASYNC_G();
            PROF(11);
            mbar_expect_tx(bars + B_ZF * 8, 20480);
            tma2d(sb + OFF_Z, &tmZ, m2 * 128, n2 * 80, bars + B_ZF * 8);
            tma2d(sb + OFF_Z + 10240, &tmZ, m2 * 128 + 64, n2 * 80, bars + B_ZF * 8);
            if (atomicAdd(&g_cnt[C_DONE * 32], 1u) == 127u) {
                for (int i = 0; i < C_NUM; i++) g_cnt[i * 32] = 0;
            }
        } else if (warp == 1 && lane == 0) {
            const int ch0 = (bid >> 4) * 80 + (bid & 15);
            auto load_h = [&](int i) {
                uint32_t cb = sb + OFF_CB + (i & 1) * CB, full = bars + (B_CRAW + (i & 1)) * 8;
                mbar_expect_tx(full, 4096);
                bulk_load(cb + CB_HA, prm.ssm_k + (ch0 + 16 * i) * SEQ, 4096, full);
            };
            auto load_x = [&](int i) {
                uint32_t cb = sb + OFF_CB + (i & 1) * CB, full = bars + (B_CFULL + (i & 1)) * 8;
                mbar_expect_tx(full, 4096);
                bulk_load(cb + CB_P0, g_kvT + (ch0 + 16 * i) * SEQ, 2048, full);
                bulk_load(cb + CB_P0 + CB_PS, g_kvT + (ch0 + 16 * i) * SEQ + 1024, 2048, full);
            };
            mbar_wait(bars + (B_FULL1 + KV_WAIT) * 8, 0);
            mbar_expect_tx(bars + B_KIN * 8, 131 * 160 + 640);
            tma2d(sb + OFF_KT, &tmK, role * 80, m1 * 128 - 3, bars + B_KIN * 8);
            bulk_load(sb + OFF_SK, prm.shift_k + role * 320, 640, bars + B_KIN * 8);
            load_h(0);
            wait_cnt(C_KV0 + (bid >> 4), 16);
            FENCE_ASYNC_G();
            load_x(0);
            mbar_wait(bars + B_PRE * 8, 0);
            load_h(1);
            wait_cnt(C_KV + (bid >> 4), 16);
            FENCE_ASYNC_G();
            load_x(1);
            for (int i = 0; i < NCH; i++) {
                mbar_wait(bars + (B_CDONE + (i & 1)) * 8, (i >> 1) & 1);
                bulk_store(g_zT + (ch0 + 16 * i) * SEQ, sb + OFF_STG, 4096);
                asm volatile("cp.async.bulk.commit_group;" ::: "memory");
                if (i + 2 < NCH) { load_h(i + 2); load_x(i + 2); }
                asm volatile("cp.async.bulk.wait_group.read 0;" ::: "memory");
                mbar_arrive(bars + B_STG * 8);
                asm volatile("cp.async.bulk.wait_group 0;" ::: "memory");
                FENCE_ASYNC_G();
                signal_cnt_bulk(C_Z + (bid >> 4));
            }
            PROF(12);
        } else if (warp == 2) {
#define PF_WAIT 8
            if (lane == 0 && PF_WAIT < 8) {
                mbar_wait(bars + (B_FULL1 + (PF_WAIT & 3)) * 8, 0);
                if (PF_WAIT >= 4) mbar_wait(bars + (B_FULL1 + (PF_WAIT & 3)) * 8, 1);
                l2_prefetch(prm.wg + bid * 5 * DF, 5 * DF * 2);
                l2_prefetch(prm.wu + bid * 5 * DF, 5 * DF * 2);
                l2_prefetch(prm.x + bid * 16 * DM, 16 * DM * 2);
                l2_prefetch(prm.wd + bid * 8640, 17280);
                l2_prefetch(prm.ssm_k + bid * 5 * SEQ, 5 * SEQ * 2);
            }
            __syncwarp();
            for (int i = 0; i < NCH; i++) {
                const uint32_t cb = sb + OFF_CB + (i & 1) * CB + lane * 16;
                mbar_wait(bars + (B_CRAW + (i & 1)) * 8, (i >> 1) & 1);
                #pragma unroll
                for (int j = 0; j < 8; j++) {
                    uint32_t x0, x1, x2, x3, pv = lds32(cb + CB_HA + j * 512 - 4);
                    asm volatile("ld.shared.v4.u32 {%0,%1,%2,%3}, [%4];" : "=r"(x0), "=r"(x1), "=r"(x2), "=r"(x3) : "r"(cb + CB_HA + j * 512));
                    asm volatile("st.shared.v4.u32 [%0], {%1,%2,%3,%4};" :: "r"(cb + CB_HB + j * 512), "r"(__byte_perm(pv, x0, 0x5432)), "r"(__byte_perm(x0, x1, 0x5432)),
                                 "r"(__byte_perm(x1, x2, 0x5432)), "r"(__byte_perm(x2, x3, 0x5432)) : "memory");
                }
                __syncwarp();
                if (lane == 0) mbar_arrive(bars + (B_CFULL + (i & 1)) * 8);
            }
        } else if (warp == 3 && lane == 0) {
            mbar_wait(bars + B_KV * 8, 0);
            signal_cnt(C_KV0 + role);
            PROF(23);
            mbar_wait(bars + B_KV1 * 8, 0);
            signal_cnt(C_KV + role);
            PROF(14);
            mbar_wait(bars + B_HD * 8, 0);
            signal_cnt(C_H1 + m1);
            if (bid < 120) {
                mbar_wait(bars + B_WD * 8, 0);
                for (int q = 0; q < 3; q++) bulk_store(g_wd + (bid * 9 + q * 3) * 1024, sb + ((2 + q) & 3) * ST1 + 40960, 6144);
                asm volatile("cp.async.bulk.commit_group;" ::: "memory");
                asm volatile("cp.async.bulk.wait_group 0;" ::: "memory");
                FENCE_ASYNC_G();
                signal_cnt_bulk(C_W);
            }
            PROF(15);
            mbar_wait(bars + B_G * 8, 0);
            mbar_wait(bars + B_HD * 8, 1);
            signal_cnt(C_H2 + m1);
        }
        if (tid == 0) { PROF(13); }
    } else if (wg == 3) {
        asm volatile("setmaxnreg.inc.sync.aligned.u32 152;\n");
        const int t = tid - 384, w = warp & 3;
        const float Dall = lane < NCH ? __bfloat162float(prm.ssm_D[(bid >> 4) * 80 + (bid & 15) + 16 * lane]) : 0.f;
        {
            const int r = lane >> 2, c = lane & 3;
            const int tb = 64 * (w >> 1) + 16 * (r >> 1) + 15 - 8 * (w & 1) - (r & 1);
            const bf16* vp = prm.v + (m1 * 128 + tb) * DM + role * 80 + c * 4;
            uint2 vv[5][4];
            mbar_wait(bars + (B_FULL1 + KV_WAIT) * 8, 0);
            #pragma unroll
            for (int g = 0; g < 5; g++)
                #pragma unroll
                for (int b = 0; b < 4; b++) vv[g][b] = __ldg((const uint2*)(vp - 2 * b * DM + g * 16));
            bf16* dst = g_kvT + (role * 80 + 4 * (r >> 1) + (r & 1)) * SEQ + (w & 1) * 1024 + (m1 * 8 + 4 * (w >> 1) + c) * 8;
            const uint32_t ka = sb + OFF_KT + (tb + 3) * 160 + c * 8, wa = sb + OFF_SK + c * 32;
            const int row0 = m1 * 128 + role * 16 + w * 4;
            uint4 gw[3], xx[4][3], sw[2][2];
            uint2 kb[2][10];
            mbar_wait(bars + B_KIN * 8, 0);
            if (t == 0) { PROF(24); }
            #pragma unroll
            for (int g = -1; g < 5; g++) {
                if (g < 4) {
                    #pragma unroll
                    for (int m = 0; m < 10; m++) asm volatile("ld.shared.v2.u32 {%0,%1}, [%2];" : "=r"(kb[(g + 1) & 1][m].x), "=r"(kb[(g + 1) & 1][m].y) : "r"(ka + (g + 1) * 32 - m * 160));
                    #pragma unroll
                    for (int j = 0; j < 2; j++) asm volatile("ld.shared.v4.u32 {%0,%1,%2,%3}, [%4];" : "=r"(sw[(g + 1) & 1][j].x), "=r"(sw[(g + 1) & 1][j].y), "=r"(sw[(g + 1) & 1][j].z), "=r"(sw[(g + 1) & 1][j].w) : "r"(wa + (g + 1) * 128 + j * 16));
                }
                if (g < 0) continue;
                const uint2* kk = kb[g & 1];
                #pragma unroll
                for (int j = 0; j < 2; j++) {
                    uint32_t s0 = sw[g & 1][j].x, s1 = sw[g & 1][j].y, s2 = sw[g & 1][j].z, s3 = sw[g & 1][j].w, o[4];
                    const uint32_t w0 = __byte_perm(s0, s2, 0x5410), w1 = __byte_perm(s0, s2, 0x7632), w2 = __byte_perm(s1, s3, 0x5410), w3 = __byte_perm(s1, s3, 0x7632);
                    #pragma unroll
                    for (int b = 0; b < 4; b++) {
                        uint32_t a = hmul2(j ? kk[2 * b + 3].y : kk[2 * b + 3].x, w3);
                        a = hfma2(j ? kk[2 * b + 2].y : kk[2 * b + 2].x, w2, a);
                        a = hfma2(j ? kk[2 * b + 1].y : kk[2 * b + 1].x, w1, a);
                        a = hfma2(j ? kk[2 * b].y : kk[2 * b].x, w0, a);
                        a = hmul2(a, j ? vv[g][b].y : vv[g][b].x);
                        asm volatile("movmatrix.sync.aligned.m8n8.trans.b16 %0, %1;" : "=r"(o[b]) : "r"(a));
                    }
                    *(uint4*)(dst + (g * 16 + 2 * j) * SEQ) = make_uint4(o[0], o[1], o[2], o[3]);
                }
                if (g == 0 || g == 4) { __syncwarp(); if (lane == 0) mbar_arrive(bars + (g ? B_KV1 : B_KV) * 8); }
                if (g == 0 && t == 0) { PROF(22); }
                if (g == 4) {
                    #pragma unroll
                    for (int j = 0; j < 3; j++) {
                        bool ok = j < 2 || lane < 16;
                        gw[j] = ok ? __ldg((const uint4*)(prm.gate_w + (j * 32 + lane) * 8)) : make_uint4(0, 0, 0, 0);
                        #pragma unroll
                        for (int q = 0; q < 4; q++) xx[q][j] = ok ? __ldg((const uint4*)(prm.x + (row0 + q) * DM + (j * 32 + lane) * 8)) : make_uint4(0, 0, 0, 0);
                    }
                }
            }
            asm volatile("bar.sync 1, 128;" ::: "memory");
            if (t == 0) { PROF(31); }
            if (w == 3) {
                if (lane < 28) zero_pad(sb + OFF_CB + CB, lane);
                __syncwarp();
                if (lane == 0) mbar_arrive(bars + B_PRE * 8);
            }
            float sum[4];
            #pragma unroll
            for (int q = 0; q < 4; q++) {
                float s = 0.f;
                #pragma unroll
                for (int j = 0; j < 3; j++) {
                    s += bf_lo(xx[q][j].x) * bf_lo(gw[j].x) + bf_hi(xx[q][j].x) * bf_hi(gw[j].x);
                    s += bf_lo(xx[q][j].y) * bf_lo(gw[j].y) + bf_hi(xx[q][j].y) * bf_hi(gw[j].y);
                    s += bf_lo(xx[q][j].z) * bf_lo(gw[j].z) + bf_hi(xx[q][j].z) * bf_hi(gw[j].z);
                    s += bf_lo(xx[q][j].w) * bf_lo(gw[j].w) + bf_hi(xx[q][j].w) * bf_hi(gw[j].w);
                }
                sum[q] = s;
            }
            float u0 = (lane & 1) ? sum[0] : sum[1], u1 = (lane & 1) ? sum[2] : sum[3];
            float a0 = ((lane & 1) ? sum[1] : sum[0]) + __shfl_xor_sync(0xffffffffu, u0, 1);
            float a1 = ((lane & 1) ? sum[3] : sum[2]) + __shfl_xor_sync(0xffffffffu, u1, 1);
            float s = ((lane & 2) ? a1 : a0) + __shfl_xor_sync(0xffffffffu, (lane & 2) ? a0 : a1, 2);
            #pragma unroll
            for (int o = 4; o < 32; o <<= 1) s += __shfl_xor_sync(0xffffffffu, s, o);
            if (lane < 4) g_gate[row0 + lane] = 1.0f / (1.0f + __expf(-s));
            __syncwarp();
            if (lane == 0) mbar_arrive(bars + B_G * 8);
        }
        if (t == 0) { PROF(25); }
        const int w0 = w & 1, w1 = w >> 1, r = lane >> 2, c = lane & 3;
        const uint32_t a_off = (r & 1) ? CB_HA + 2 * (32 * w1 + 8 * w0 + r - 15 + 2 * c) : CB_HB + 2 * (32 * w1 + 8 * w0 + r - 14 + 2 * c);
        const uint32_t stg = sb + OFF_STG;
        for (int i = 0; i < NCH; i++) {
            const uint32_t cb = sb + OFF_CB + (i & 1) * CB;
            const float Dv = __shfl_sync(0xffffffffu, Dall, i);
            mbar_wait(bars + (B_CFULL + (i & 1)) * 8, (i >> 1) & 1);
            if (t == 0) { PROF(16 + i); }
            float hi64[32], t48[24], t32[16], t16[8], lo64[32], lo48[24], lo32[16], lo16[8];
            uint32_t a0[16], a1[16], a2[16];
            const uint64_t db0 = make_desc(cb + CB_P0, CB_PS, 128, 0);
            const uint32_t aa = cb + a_off;
            conv_loadA(a0, aa + 7 * 512);
            conv_loadA(a1, aa + 6 * 512);
            conv_loadA(a2, aa + 5 * 512);
            conv_group<16, 0>(t16, a0, db0);
            conv_group<32, 0>(t32, a1, db0);
            WG_WAIT(1); AFENCE(a0); conv_loadA(a0, aa + 4 * 512);
            conv_group<48, 0>(t48, a2, db0);
            WG_WAIT(1); AFENCE(a1); conv_loadA(a1, aa + 3 * 512);
            acc_fence<8>(t16); acc_fence<16>(t32);
            #pragma unroll
            for (int j = 0; j < 8; j++) t32[8 + j] += t16[j];
            WG_WAIT(0); AFENCE(a2); conv_loadA(a2, aa + 2 * 512);
            acc_fence<24>(t48);
            #pragma unroll
            for (int j = 0; j < 16; j++) t48[8 + j] += t32[j];
            acc_widen<24>(hi64, t48);
            conv_group<64, 1>(hi64, a0, db0);
            conv_group<16, 0>(lo16, a1, db0);
            conv_group<64, 1>(hi64, a1, db0 + 16);
            WG_WAIT(1); AFENCE(a0); conv_loadA(a0, aa + 1 * 512); acc_widen<8>(lo32, lo16);
            conv_group<32, 1>(lo32, a2, db0);
            conv_group<64, 1>(hi64, a2, db0 + 32);
            WG_WAIT(1); AFENCE(a1); conv_loadA(a1, aa); acc_widen<16>(lo48, lo32);
            conv_group<48, 1>(lo48, a0, db0);
            conv_group<64, 1>(hi64, a0, db0 + 48);
            WG_WAIT(1); AFENCE(a2); acc_widen<24>(lo64, lo48);
            conv_group<64, 1>(lo64, a1, db0);
            conv_group<64, 1>(hi64, a1, db0 + 64);
            WG_WAIT(0);
            AFENCE(a0); AFENCE(a1);
            acc_fence<32>(lo64); acc_fence<32>(hi64);
            if (t == 0 && i == CI) { PROF(26); }
            float acc[64];
            #pragma unroll
            for (int j = 0; j < 32; j++) { acc[j] = lo64[j]; acc[32 + j] = hi64[j]; }
            #pragma unroll
            for (int q = 15; q >= 1; q--) { acc[4 * q] += acc[4 * q - 2]; acc[4 * q + 1] += acc[4 * q - 1]; }
            asm volatile("bar.sync 1, 128;" ::: "memory");
            const uint32_t xs1 = cb + CB_HA + w0 * 2048, xs0 = cb + CB_HB + w0 * 2048;
            if (w1 == 0) {
                #pragma unroll
                for (int q = 8; q < 16; q++) sts64f(xs0 + (q - 8) * 256 + lane * 8, acc[4 * q], acc[4 * q + 1]);
            } else {
                #pragma unroll
                for (int q = 0; q < 8; q++) sts64f(xs1 + q * 256 + lane * 8, acc[4 * q], acc[4 * q + 1]);
            }
            if (i > 0) mbar_wait(bars + B_STG * 8, (i - 1) & 1);
            asm volatile("bar.sync 1, 128;" ::: "memory");
            if (t == 0 && i == CI) { PROF(27); }
            const uint32_t kvp = cb + CB_P0 + (1 - w0) * CB_PS + (7 - r) * 2 + c * 32;
            uint32_t pk[8];
            if (w1 == 0) {
                const uint32_t rd = xs1 + (c > 0 ? lane * 8 - 8 : lane * 8 + 24 - 256);
                #pragma unroll
                for (int q = 0; q < 9; q++) {
                    float2 o = make_float2(0.f, 0.f);
                    if (q == 0) { if (c > 0) o = lds64f(rd); }
                    else if (q == 8) { if (c == 0) o = lds64f(rd + q * 256); }
                    else o = lds64f(rd + q * 256);
                    float z0 = fmaf(Dv, lds_bf(kvp + q * 128), acc[4 * q] + o.x);
                    float z1 = fmaf(Dv, lds_bf(kvp + q * 128 + 16), acc[4 * q + 1] + o.y);
                    uint32_t pz = pack2(z0, z1);
                    if (q < 8) pk[q] = pz;
                    else if (c == 0) {
                        asm volatile("st.shared.u16 [%0], %1;" :: "r"(stg + 64 * 32 + w0 * 16 + r * 2), "h"((uint16_t)(pz & 0xFFFF)) : "memory");
                        asm volatile("st.shared.u16 [%0], %1;" :: "r"(stg + 65 * 32 + w0 * 16 + r * 2), "h"((uint16_t)(pz >> 16)) : "memory");
                    }
                }
                stsm4_t(stg + lane * 32 + w0 * 16, pk[0], pk[1], pk[2], pk[3]);
                stsm4_t(stg + (32 + lane) * 32 + w0 * 16, pk[4], pk[5], pk[6], pk[7]);
            } else {
                const uint32_t rd = xs0 + (c < 3 ? lane * 8 + 8 : lane * 8 - 24 + 256);
                #pragma unroll
                for (int q = 8; q < 16; q++) {
                    float2 o = make_float2(0.f, 0.f);
                    float k0 = 0.f, k1 = 0.f;
                    if (q < 15 || c < 3) { o = lds64f(rd + (q - 8) * 256); k0 = lds_bf(kvp + q * 128 + 32); k1 = lds_bf(kvp + q * 128 + 48); }
                    pk[q - 8] = pack2(fmaf(Dv, k0, acc[4 * q] + o.x), fmaf(Dv, k1, acc[4 * q + 1] + o.y));
                }
                stsm4_t(stg + (66 + lane) * 32 + w0 * 16, pk[0], pk[1], pk[2], pk[3]);
                stsm4_t(stg + (98 + lane) * 32 + w0 * 16, pk[4], pk[5], pk[6], pk[7]);
            }
            FENCE_ASYNC_S();
            __syncwarp();
            if (lane == 0) mbar_arrive(bars + (B_CDONE + (i & 1)) * 8);
            if (t == 0 && i == CI) { PROF(28); }
        }
        if (t == 0) { PROF(21); }
    } else {
        asm volatile("setmaxnreg.inc.sync.aligned.u32 160;\n");
        const int cw = wg - 1, t = tid & 127, w = warp & 3, r = lane >> 2, c = lane & 3;
        {
            float d[128];
            if (cw == 1) PP_ARRIVE();
            for (int it = 0; it < 10; it++) {
                int st = it & 3;
                mbar_wait(bars + (B_FULL1 + st) * 8, (it >> 2) & 1);
                if (it == 0 && tid == 128) { PROF(0); }
                uint64_t da = make_desc(sb + st * ST1 + cw * 8192, 16, 1024, 1);
                uint64_t db = make_desc(sb + st * ST1 + 16384, 8192, 1024, 1);
                PP_SYNC();
                WG_FENCE();
                #pragma unroll
                for (int k = 0; k < 4; k++) {
                    wgmma_ss_n128(d, da + k * 2, db + k * 128, (it | k) != 0);
                    wgmma_ss_n128(d + 64, da + k * 2, db + 1024 + k * 128, (it | k) != 0);
                }
                WG_COMMIT();
                PP_ARRIVE();
                WG_WAIT(0);
                if (t < 2) mbar_arrive_cluster(bars + (B_EMPTY1 + st) * 8, t);
            }
            WG_WAIT(0);
            #pragma unroll
            for (int j = 0; j < 128; j++) asm volatile("" : "+f"(d[j]) :: "memory");
            if (tid == 128) { PROF(1); }
            bf16* hrow = g_h + m1 * 27 * 8192 + cw * 4096 + w * 1024 + c * 64 + r * 8;
            #pragma unroll
            for (int G = 0; G < 4; G++) {
                #pragma unroll
                for (int hf = 0; hf < 2; hf++) {
                    uint32_t p[4];
                    #pragma unroll
                    for (int q = 0; q < 4; q++) {
                        int j = (G * 4 + q) * 4 + hf * 2;
                        p[q] = pack2(geglu(d[j], d[64 + j]), geglu(d[j + 1], d[64 + j + 1]));
                    }
                    *(uint4*)(hrow + hf * 512 + (role * 2 + (G >> 1)) * 8192 + (G & 1) * 256) = make_uint4(p[0], p[1], p[2], p[3]);
                }
            }
            __syncwarp();
            if (lane == 0) mbar_arrive(bars + B_HD * 8);
            if (tid == 128) { PROF(2); }
            float d2[96];
            for (int it = 10; it < 20; it++) {
                int st = it & 3;
                mbar_wait(bars + (B_FULL1 + st) * 8, (it >> 2) & 1);
                uint64_t da = make_desc(sb + st * ST1 + cw * 8192, 16, 1024, 1);
                uint64_t db = make_desc(sb + st * ST1 + 16384, 4096, 512, 2);
                PP_SYNC();
                WG_FENCE();
                #pragma unroll
                for (int k = 0; k < 4; k++) {
                    wgmma_ss_n192(d2, da + k * 2, db + k * 64, ((it - 10) | k) != 0);
                }
                WG_COMMIT();
                PP_ARRIVE();
                WG_WAIT(0);
                if (t < 2) mbar_arrive_cluster(bars + (B_EMPTY1 + st) * 8, t);
            }
            WG_WAIT(0);
            #pragma unroll
            for (int j = 0; j < 96; j++) asm volatile("" : "+f"(d2[j]) :: "memory");
            if (tid == 128) { PROF(3); }
            #pragma unroll
            for (int G = 0; G < 3; G++) {
                int Gg = 32 + role * 3 + G;
                if (Gg < DF / 32) {
                    #pragma unroll
                    for (int hf = 0; hf < 2; hf++) {
                        uint32_t p[4];
                        #pragma unroll
                        for (int q = 0; q < 4; q++) {
                            int j = (G * 4 + q) * 4 + hf * 2;
                            p[q] = pack2(geglu(d2[j], d2[48 + j]), geglu(d2[j + 1], d2[48 + j + 1]));
                        }
                        *(uint4*)(hrow + hf * 512 + (Gg >> 1) * 8192 + (Gg & 1) * 256) = make_uint4(p[0], p[1], p[2], p[3]);
                    }
                }
            }
            __syncwarp();
            if (lane == 0) mbar_arrive(bars + B_HD * 8);
            if (tid == 128) { PROF(4); }
        }
        float e[40];
        {
            float f[80];
            int st = 0; uint32_t ph = 0;
            for (int it = 0; it < 13; it++) {
                mbar_wait(bars + (B_FULL2 + st) * 8, ph);
                uint64_t da = make_desc(sb + st * ST2 + cw * 8192, 128, 1024, 0);
                uint64_t db = make_desc(sb + st * ST2 + 16384, 2048, 256, 3);
                PP_SYNC();
                WG_FENCE();
                #pragma unroll
                for (int k = 0; k < 4; k++) wgmma_ss_n160(f, da + k * 16, db + k * 32, (it | k) != 0);
                WG_COMMIT();
                if (cw == 0 || it < 12) PP_ARRIVE();
                WG_WAIT(0);
                if (t == 0) mbar_arrive(bars + (B_EMPTY2 + st) * 8);
                if (it == 11 && t == 32) mbar_arrive_cluster(bars + B_XFREE * 8, rank ^ 1);
                if (++st == NST2) { st = 0; ph ^= 1; }
            }
            WG_WAIT(0);
            #pragma unroll
            for (int j = 0; j < 80; j++) asm volatile("" : "+f"(f[j]) :: "memory");
            if (tid == 128) { PROF(5); }
            uint32_t xa = sb + cw * 20480 + t * 16, xb = bars + (B_XF + cw) * 8, ra, rb;
            asm volatile("mapa.shared::cluster.u32 %0, %1, %2;" : "=r"(ra) : "r"(xa), "r"(rank ^ 1));
            asm volatile("mapa.shared::cluster.u32 %0, %1, %2;" : "=r"(rb) : "r"(xb), "r"(rank ^ 1));
            #pragma unroll
            for (int j = 0; j < 40; j++) e[j] = rank ? f[40 + j] : f[j];
            mbar_wait(bars + (B_FULL2 + 3) * 8, 0);
            {
                uint64_t da = make_desc(sb + 3 * ST2 + cw * 8192, 128, 1024, 0);
                uint64_t db = make_desc(sb + 3 * ST2 + 16384, 2048, 256, 3);
                WG_FENCE();
                #pragma unroll
                for (int k = 0; k < 4; k++) wgmma_ss_n80(e, da + k * 16, db + k * 32, 1);
                WG_COMMIT();
            }
            mbar_wait(bars + B_XFREE * 8, 0);
            #pragma unroll
            for (int j = 0; j < 10; j++) {
                float s0 = rank ? f[4 * j] : f[40 + 4 * j], s1 = rank ? f[4 * j + 1] : f[41 + 4 * j], s2 = rank ? f[4 * j + 2] : f[42 + 4 * j], s3 = rank ? f[4 * j + 3] : f[43 + 4 * j];
                asm volatile("st.async.weak.shared::cluster.mbarrier::complete_tx::bytes.v4.f32 [%0], {%1,%2,%3,%4}, [%5];"
                    :: "r"(ra + j * 2048), "f"(s0), "f"(s1), "f"(s2), "f"(s3), "r"(rb) : "memory");
            }
            WG_WAIT(0);
            acc_fence<40>(e);
            mbar_wait(xb, 0);
            #pragma unroll
            for (int j = 0; j < 10; j++) {
                float s0, s1, s2, s3;
                asm volatile("ld.shared.v4.f32 {%0,%1,%2,%3}, [%4];" : "=f"(s0), "=f"(s1), "=f"(s2), "=f"(s3) : "r"(xa + j * 2048) : "memory");
                e[4 * j] += s0; e[4 * j + 1] += s1; e[4 * j + 2] += s2; e[4 * j + 3] += s3;
            }
        }
        if (tid == 128) { PROF(30); }
        mbar_wait(bars + B_QF * 8, 0);
        const int row = m2 * 128 + cw * 64 + w * 16 + r;
        float g0 = __ldcg(&g_gate[row]), g1 = __ldcg(&g_gate[row + 8]);
        mbar_wait(bars + B_ZF * 8, 0);
        if (tid == 128) { PROF(6); }
        const int mi = lane >> 3, l8 = lane & 7;
        const uint32_t qa = sb + OFF_Q + (cw * 64 + w * 16 + (mi & 1) * 8 + l8) * 160 + (mi >> 1) * 16;
        const uint32_t za = sb + OFF_Z + cw * 10240 + ((mi >> 1) * 8 + l8) * 128 + (((2 * w + (mi & 1)) ^ l8) << 4);
        #pragma unroll
        for (int j = 0; j < 10; j += 2) {
            uint32_t qv[4], zv[4], o[4];
            ldsm4(qa + j * 16, qv);
            ldsm4_t(za + j * 1024, zv);
            #pragma unroll
            for (int u = 0; u < 4; u++) {
                float g = (u & 1) ? g1 : g0;
                int ei = (j + (u >> 1)) * 4 + (u & 1) * 2;
                float b0 = e[ei], b1 = e[ei + 1];
                float a0 = bf_lo(qv[u]) * bf_lo(zv[u]), a1 = bf_hi(qv[u]) * bf_hi(zv[u]);
                o[u] = pack2(fmaf(g, a0 - b0, b0), fmaf(g, a1 - b1, b1));
            }
            stsm4(qa + j * 16, o[0], o[1], o[2], o[3]);
        }
        FENCE_ASYNC_S();
        __syncwarp();
        if (lane == 0) {
            tma2d_store(&tmO, sb + OFF_Q + (cw * 64 + w * 16) * 160, n2 * 80, m2 * 128 + cw * 64 + w * 16);
            asm volatile("cp.async.bulk.commit_group;" ::: "memory");
            asm volatile("cp.async.bulk.wait_group.read 0;" ::: "memory");
        }
        if (tid == 128) { PROF(7); }
    }
}

#define CHK(x) (x)
typedef CUresult (*EncodeFn)(CUtensorMap*, CUtensorMapDataType, cuuint32_t, void*, const cuuint64_t*, const cuuint64_t*, const cuuint32_t*, const cuuint32_t*,
                             CUtensorMapInterleave, CUtensorMapSwizzle, CUtensorMapL2promotion, CUtensorMapFloatOOBfill);
static void mk2d(EncodeFn enc, CUtensorMap* m, const void* p, uint64_t d0, uint64_t d1, uint32_t b0, uint32_t b1, CUtensorMapSwizzle sw) {
    cuuint64_t gd[2] = {d0, d1}; cuuint64_t gs[1] = {d0 * 2}; cuuint32_t bd[2] = {b0, b1}; cuuint32_t es[2] = {1, 1};
    CHK(enc(m, CU_TENSOR_MAP_DATA_TYPE_BFLOAT16, 2, (void*)p, gd, gs, bd, es, CU_TENSOR_MAP_INTERLEAVE_NONE, sw, CU_TENSOR_MAP_L2_PROMOTION_L2_256B, CU_TENSOR_MAP_FLOAT_OOB_FILL_NONE));
}

extern "C" void kernel_launch(void* const* d_in, const int* in_sizes, int n_in, void* d_out, int out_size) {
    static EncodeFn enc = nullptr;
    static void* p_z = nullptr;
    if (!enc) {
        void* fn = nullptr; cudaDriverEntryPointQueryResult qr;
        cudaGetDriverEntryPoint("cuTensorMapEncodeTiled", &fn, cudaEnableDefault, &qr);
        enc = (EncodeFn)fn;
        cudaGetSymbolAddress(&p_z, g_zT);
        cudaFuncSetAttribute(fused_kernel, cudaFuncAttributeMaxDynamicSharedMemorySize, SMEM_TOTAL);
    }
    CUtensorMap tX, tWg, tWu, tWg2, tWu2, tWd, tK, tQ, tZ, tO;
    for (int i = 0; i < 2; i++) {
        cuuint64_t gd[3] = {32, DM, 54}; cuuint64_t gs[2] = {DF * 2, 64}; cuuint32_t bd[3] = {32, 64, 3}; cuuint32_t es[3] = {1, 1, 1};
        CHK(enc(i ? &tWu2 : &tWg2, CU_TENSOR_MAP_DATA_TYPE_BFLOAT16, 3, d_in[7 + i], gd, gs, bd, es, CU_TENSOR_MAP_INTERLEAVE_NONE, CU_TENSOR_MAP_SWIZZLE_64B,
            CU_TENSOR_MAP_L2_PROMOTION_L2_256B, CU_TENSOR_MAP_FLOAT_OOB_FILL_NONE));
    }
    {
        cuuint64_t gd[5] = {DM, 2, 4, 4, 54}; cuuint64_t gs[4] = {1280, 10240, 2560, 40960};
        cuuint32_t bd[5] = {16, 2, 4, 4, 2}; cuuint32_t es[5] = {1, 1, 1, 1, 1};
        CHK(enc(&tWd, CU_TENSOR_MAP_DATA_TYPE_BFLOAT16, 5, d_in[9], gd, gs, bd, es, CU_TENSOR_MAP_INTERLEAVE_NONE, CU_TENSOR_MAP_SWIZZLE_32B,
            CU_TENSOR_MAP_L2_PROMOTION_L2_256B, CU_TENSOR_MAP_FLOAT_OOB_FILL_NONE));
    }
    mk2d(enc, &tK, d_in[1], DM, SEQ, 80, 131, CU_TENSOR_MAP_SWIZZLE_NONE);
    mk2d(enc, &tX, d_in[0], DM, SEQ, 64, 128, CU_TENSOR_MAP_SWIZZLE_128B);
    mk2d(enc, &tWg, d_in[7], DF, DM, 64, 64, CU_TENSOR_MAP_SWIZZLE_128B);
    mk2d(enc, &tWu, d_in[8], DF, DM, 64, 64, CU_TENSOR_MAP_SWIZZLE_128B);
    mk2d(enc, &tQ, d_in[0], DM, SEQ, 80, 128, CU_TENSOR_MAP_SWIZZLE_NONE);
    mk2d(enc, &tZ, p_z, SEQ, DM, 64, 80, CU_TENSOR_MAP_SWIZZLE_128B);
    mk2d(enc, &tO, d_out, DM, SEQ, 80, 16, CU_TENSOR_MAP_SWIZZLE_NONE);
    Params prm;
    prm.x = (const bf16*)d_in[0]; prm.k = (const bf16*)d_in[1]; prm.v = (const bf16*)d_in[2]; prm.shift_k = (const bf16*)d_in[3];
    prm.ssm_k = (const bf16*)d_in[4]; prm.ssm_D = (const bf16*)d_in[5]; prm.gate_w = (const bf16*)d_in[10]; prm.wd = (const bf16*)d_in[9]; prm.wg = (const bf16*)d_in[7]; prm.wu = (const bf16*)d_in[8];
    fused_kernel<<<128, 512, SMEM_TOTAL>>>(tX, tWg, tWu, tWg2, tWu2, tWd, tK, tQ, tZ, tO, prm);
}
```

```cpp
#include <cuda_runtime.h>
#include <cuda.h>
#include <cuda_bf16.h>
#include <stdint.h>

typedef __nv_bfloat16 bf16;
constexpr int SEQ = 2048, DM = 640, DF = 1728;

__device__ __align__(1024) bf16 g_h[SEQ * DF];
__device__ __align__(1024) bf16 g_kvT[DM * SEQ];
__device__ __align__(1024) bf16 g_zT[DM * SEQ];
__device__ __align__(1024) bf16 g_wd[DF * DM];
__device__ __align__(128) float g_gate[SEQ];
constexpr int C_KV = 0, C_KV0 = 8, C_ZL = 16, C_H1 = 24, C_H2 = 40, C_Z = 56, C_DONE = 64, C_W = 65, C_NUM = 66;
__device__ unsigned g_cnt[C_NUM * 32];
#define PROF(i)

constexpr int ST1 = 49152, NST1 = 4;
constexpr int ST2 = 36864, NST2 = 5, OFF_Q = 4 * ST2, OFF_Z = OFF_Q + 20480;
constexpr int RING = ST1 * NST1;
constexpr int CB_HB = 128, CB_HA = 4288, CB_P0 = 9280, CB_PS = 2944, CB = 14336;
constexpr int OFF_CB = RING;
constexpr int OFF_STG = OFF_CB + 2 * CB;
constexpr int OFF_KT = OFF_CB + CB, OFF_SK = OFF_CB + CB_P0 - 896;
constexpr int OFF_GW = OFF_CB + 32896, OFF_HS = 3 * ST1;
constexpr int OFF_BAR = OFF_KT + 20992;
constexpr int SMEM_TOTAL = OFF_BAR + 384;
constexpr int B_FULL1 = 0, B_EMPTY1 = 4, B_FULL2 = 8, B_EMPTY2 = 15, B_CFULL = 22, B_CDONE = 24, B_STG = 26, B_KV = 27, B_G = 28, B_CRAW = 29, B_HD = 31, B_WD = 32, B_KIN = 33, B_PRE = 34, B_QF = 13, B_ZF = 14, B_XFREE = 20, B_XF = 35, B_KV1 = 21;
#define CI 3
constexpr int NCH = 5;

#define KV_WAIT 0
#define V_WAIT -1
__device__ __forceinline__ void wgmma_ss_n128(float* d, uint64_t da, uint64_t db, int sd) {
    asm volatile("{\n.reg .pred p;\nsetp.ne.b32 p, %66, 0;\nwgmma.mma_async.sync.aligned.m64n128k16.f32.bf16.bf16 {%0,%1,%2,%3,%4,%5,%6,%7,%8,%9,%10,%11,%12,%13,%14,%15,%16,%17,%18,%19,%20,%21,%22,%23,%24,%25,%26,%27,%28,%29,%30,%31,%32,%33,%34,%35,%36,%37,%38,%39,%40,%41,%42,%43,%44,%45,%46,%47,%48,%49,%50,%51,%52,%53,%54,%55,%56,%57,%58,%59,%60,%61,%62,%63}, %64, %65, p, 1, 1, 0, 1;\n}\n"
    : "+f"(d[0]),"+f"(d[1]),"+f"(d[2]),"+f"(d[3]),"+f"(d[4]),"+f"(d[5]),"+f"(d[6]),"+f"(d[7]),"+f"(d[8]),"+f"(d[9]),"+f"(d[10]),"+f"(d[11]),"+f"(d[12]),"+f"(d[13]),"+f"(d[14]),"+f"(d[15]),"+f"(d[16]),"+f"(d[17]),"+f"(d[18]),"+f"(d[19]),"+f"(d[20]),"+f"(d[21]),"+f"(d[22]),"+f"(d[23]),"+f"(d[24]),"+f"(d[25]),"+f"(d[26]),"+f"(d[27]),"+f"(d[28]),"+f"(d[29]),"+f"(d[30]),"+f"(d[31]),"+f"(d[32]),"+f"(d[33]),"+f"(d[34]),"+f"(d[35]),"+f"(d[36]),"+f"(d[37]),"+f"(d[38]),"+f"(d[39]),"+f"(d[40]),"+f"(d[41]),"+f"(d[42]),"+f"(d[43]),"+f"(d[44]),"+f"(d[45]),"+f"(d[46]),"+f"(d[47]),"+f"(d[48]),"+f"(d[49]),"+f"(d[50]),"+f"(d[51]),"+f"(d[52]),"+f"(d[53]),"+f"(d[54]),"+f"(d[55]),"+f"(d[56]),"+f"(d[57]),"+f"(d[58]),"+f"(d[59]),"+f"(d[60]),"+f"(d[61]),"+f"(d[62]),"+f"(d[63]) : "l"(da), "l"(db), "r"(sd));
}
__device__ __forceinline__ void wgmma_ss_n192(float* d, uint64_t da, uint64_t db, int sd) {
    asm volatile("{\n.reg .pred p;\nsetp.ne.b32 p, %98, 0;\nwgmma.mma_async.sync.aligned.m64n192k16.f32.bf16.bf16 {%0,%1,%2,%3,%4,%5,%6,%7,%8,%9,%10,%11,%12,%13,%14,%15,%16,%17,%18,%19,%20,%21,%22,%23,%24,%25,%26,%27,%28,%29,%30,%31,%32,%33,%34,%35,%36,%37,%38,%39,%40,%41,%42,%43,%44,%45,%46,%47,%48,%49,%50,%51,%52,%53,%54,%55,%56,%57,%58,%59,%60,%61,%62,%63,%64,%65,%66,%67,%68,%69,%70,%71,%72,%73,%74,%75,%76,%77,%78,%79,%80,%81,%82,%83,%84,%85,%86,%87,%88,%89,%90,%91,%92,%93,%94,%95}, %96, %97, p, 1, 1, 0, 1;\n}\n"
    : "+f"(d[0]),"+f"(d[1]),"+f"(d[2]),"+f"(d[3]),"+f"(d[4]),"+f"(d[5]),"+f"(d[6]),"+f"(d[7]),"+f"(d[8]),"+f"(d[9]),"+f"(d[10]),"+f"(d[11]),"+f"(d[12]),"+f"(d[13]),"+f"(d[14]),"+f"(d[15]),"+f"(d[16]),"+f"(d[17]),"+f"(d[18]),"+f"(d[19]),"+f"(d[20]),"+f"(d[21]),"+f"(d[22]),"+f"(d[23]),"+f"(d[24]),"+f"(d[25]),"+f"(d[26]),"+f"(d[27]),"+f"(d[28]),"+f"(d[29]),"+f"(d[30]),"+f"(d[31]),"+f"(d[32]),"+f"(d[33]),"+f"(d[34]),"+f"(d[35]),"+f"(d[36]),"+f"(d[37]),"+f"(d[38]),"+f"(d[39]),"+f"(d[40]),"+f"(d[41]),"+f"(d[42]),"+f"(d[43]),"+f"(d[44]),"+f"(d[45]),"+f"(d[46]),"+f"(d[47]),"+f"(d[48]),"+f"(d[49]),"+f"(d[50]),"+f"(d[51]),"+f"(d[52]),"+f"(d[53]),"+f"(d[54]),"+f"(d[55]),"+f"(d[56]),"+f"(d[57]),"+f"(d[58]),"+f"(d[59]),"+f"(d[60]),"+f"(d[61]),"+f"(d[62]),"+f"(d[63]),"+f"(d[64]),"+f"(d[65]),"+f"(d[66]),"+f"(d[67]),"+f"(d[68]),"+f"(d[69]),"+f"(d[70]),"+f"(d[71]),"+f"(d[72]),"+f"(d[73]),"+f"(d[74]),"+f"(d[75]),"+f"(d[76]),"+f"(d[77]),"+f"(d[78]),"+f"(d[79]),"+f"(d[80]),"+f"(d[81]),"+f"(d[82]),"+f"(d[83]),"+f"(d[84]),"+f"(d[85]),"+f"(d[86]),"+f"(d[87]),"+f"(d[88]),"+f"(d[89]),"+f"(d[90]),"+f"(d[91]),"+f"(d[92]),"+f"(d[93]),"+f"(d[94]),"+f"(d[95]) : "l"(da), "l"(db), "r"(sd));
}
__device__ __forceinline__ void wgmma_ss_n160(float* d, uint64_t da, uint64_t db, int sd) {
    asm volatile("{\n.reg .pred p;\nsetp.ne.b32 p, %82, 0;\nwgmma.mma_async.sync.aligned.m64n160k16.f32.bf16.bf16 {%0,%1,%2,%3,%4,%5,%6,%7,%8,%9,%10,%11,%12,%13,%14,%15,%16,%17,%18,%19,%20,%21,%22,%23,%24,%25,%26,%27,%28,%29,%30,%31,%32,%33,%34,%35,%36,%37,%38,%39,%40,%41,%42,%43,%44,%45,%46,%47,%48,%49,%50,%51,%52,%53,%54,%55,%56,%57,%58,%59,%60,%61,%62,%63,%64,%65,%66,%67,%68,%69,%70,%71,%72,%73,%74,%75,%76,%77,%78,%79}, %80, %81, p, 1, 1, 0, 1;\n}\n"
    : "+f"(d[0]),"+f"(d[1]),"+f"(d[2]),"+f"(d[3]),"+f"(d[4]),"+f"(d[5]),"+f"(d[6]),"+f"(d[7]),"+f"(d[8]),"+f"(d[9]),"+f"(d[10]),"+f"(d[11]),"+f"(d[12]),"+f"(d[13]),"+f"(d[14]),"+f"(d[15]),"+f"(d[16]),"+f"(d[17]),"+f"(d[18]),"+f"(d[19]),"+f"(d[20]),"+f"(d[21]),"+f"(d[22]),"+f"(d[23]),"+f"(d[24]),"+f"(d[25]),"+f"(d[26]),"+f"(d[27]),"+f"(d[28]),"+f"(d[29]),"+f"(d[30]),"+f"(d[31]),"+f"(d[32]),"+f"(d[33]),"+f"(d[34]),"+f"(d[35]),"+f"(d[36]),"+f"(d[37]),"+f"(d[38]),"+f"(d[39]),"+f"(d[40]),"+f"(d[41]),"+f"(d[42]),"+f"(d[43]),"+f"(d[44]),"+f"(d[45]),"+f"(d[46]),"+f"(d[47]),"+f"(d[48]),"+f"(d[49]),"+f"(d[50]),"+f"(d[51]),"+f"(d[52]),"+f"(d[53]),"+f"(d[54]),"+f"(d[55]),"+f"(d[56]),"+f"(d[57]),"+f"(d[58]),"+f"(d[59]),"+f"(d[60]),"+f"(d[61]),"+f"(d[62]),"+f"(d[63]),"+f"(d[64]),"+f"(d[65]),"+f"(d[66]),"+f"(d[67]),"+f"(d[68]),"+f"(d[69]),"+f"(d[70]),"+f"(d[71]),"+f"(d[72]),"+f"(d[73]),"+f"(d[74]),"+f"(d[75]),"+f"(d[76]),"+f"(d[77]),"+f"(d[78]),"+f"(d[79]) : "l"(da), "l"(db), "r"(sd));
}
__device__ __forceinline__ void wgmma_ss_n80(float* d, uint64_t da, uint64_t db, int sd) {
    asm volatile("{\n.reg .pred p;\nsetp.ne.b32 p, %42, 0;\nwgmma.mma_async.sync.aligned.m64n80k16.f32.bf16.bf16 {%0,%1,%2,%3,%4,%5,%6,%7,%8,%9,%10,%11,%12,%13,%14,%15,%16,%17,%18,%19,%20,%21,%22,%23,%24,%25,%26,%27,%28,%29,%30,%31,%32,%33,%34,%35,%36,%37,%38,%39}, %40, %41, p, 1, 1, 0, 1;\n}\n"
    : "+f"(d[0]),"+f"(d[1]),"+f"(d[2]),"+f"(d[3]),"+f"(d[4]),"+f"(d[5]),"+f"(d[6]),"+f"(d[7]),"+f"(d[8]),"+f"(d[9]),"+f"(d[10]),"+f"(d[11]),"+f"(d[12]),"+f"(d[13]),"+f"(d[14]),"+f"(d[15]),"+f"(d[16]),"+f"(d[17]),"+f"(d[18]),"+f"(d[19]),"+f"(d[20]),"+f"(d[21]),"+f"(d[22]),"+f"(d[23]),"+f"(d[24]),"+f"(d[25]),"+f"(d[26]),"+f"(d[27]),"+f"(d[28]),"+f"(d[29]),"+f"(d[30]),"+f"(d[31]),"+f"(d[32]),"+f"(d[33]),"+f"(d[34]),"+f"(d[35]),"+f"(d[36]),"+f"(d[37]),"+f"(d[38]),"+f"(d[39]) : "l"(da), "l"(db), "r"(sd));
}
template<int SD> __device__ __forceinline__ void wgmma_rs_n16(float* d, const uint32_t* a, uint64_t db) {
    asm volatile("wgmma.mma_async.sync.aligned.m64n16k16.f32.bf16.bf16 {%0,%1,%2,%3,%4,%5,%6,%7}, {%8,%9,%10,%11}, %12, %13, 1, 1, 0;\n"
    : "+f"(d[0]),"+f"(d[1]),"+f"(d[2]),"+f"(d[3]),"+f"(d[4]),"+f"(d[5]),"+f"(d[6]),"+f"(d[7]) : "r"(a[0]), "r"(a[1]), "r"(a[2]), "r"(a[3]), "l"(db), "n"(SD));
}
template<int SD> __device__ __forceinline__ void wgmma_rs_n32(float* d, const uint32_t* a, uint64_t db) {
    asm volatile("wgmma.mma_async.sync.aligned.m64n32k16.f32.bf16.bf16 {%0,%1,%2,%3,%4,%5,%6,%7,%8,%9,%10,%11,%12,%13,%14,%15}, {%16,%17,%18,%19}, %20, %21, 1, 1, 0;\n"
    : "+f"(d[0]),"+f"(d[1]),"+f"(d[2]),"+f"(d[3]),"+f"(d[4]),"+f"(d[5]),"+f"(d[6]),"+f"(d[7]),"+f"(d[8]),"+f"(d[9]),"+f"(d[10]),"+f"(d[11]),"+f"(d[12]),"+f"(d[13]),"+f"(d[14]),"+f"(d[15]) : "r"(a[0]), "r"(a[1]), "r"(a[2]), "r"(a[3]), "l"(db), "n"(SD));
}
template<int SD> __device__ __forceinline__ void wgmma_rs_n48(float* d, const uint32_t* a, uint64_t db) {
    asm volatile("wgmma.mma_async.sync.aligned.m64n48k16.f32.bf16.bf16 {%0,%1,%2,%3,%4,%5,%6,%7,%8,%9,%10,%11,%12,%13,%14,%15,%16,%17,%18,%19,%20,%21,%22,%23}, {%24,%25,%26,%27}, %28, %29, 1, 1, 0;\n"
    : "+f"(d[0]),"+f"(d[1]),"+f"(d[2]),"+f"(d[3]),"+f"(d[4]),"+f"(d[5]),"+f"(d[6]),"+f"(d[7]),"+f"(d[8]),"+f"(d[9]),"+f"(d[10]),"+f"(d[11]),"+f"(d[12]),"+f"(d[13]),"+f"(d[14]),"+f"(d[15]),"+f"(d[16]),"+f"(d[17]),"+f"(d[18]),"+f"(d[19]),"+f"(d[20]),"+f"(d[21]),"+f"(d[22]),"+f"(d[23]) : "r"(a[0]), "r"(a[1]), "r"(a[2]), "r"(a[3]), "l"(db), "n"(SD));
}
template<int SD> __device__ __forceinline__ void wgmma_rs_n64(float* d, const uint32_t* a, uint64_t db) {
    asm volatile("wgmma.mma_async.sync.aligned.m64n64k16.f32.bf16.bf16 {%0,%1,%2,%3,%4,%5,%6,%7,%8,%9,%10,%11,%12,%13,%14,%15,%16,%17,%18,%19,%20,%21,%22,%23,%24,%25,%26,%27,%28,%29,%30,%31}, {%32,%33,%34,%35}, %36, %37, 1, 1, 0;\n"
    : "+f"(d[0]),"+f"(d[1]),"+f"(d[2]),"+f"(d[3]),"+f"(d[4]),"+f"(d[5]),"+f"(d[6]),"+f"(d[7]),"+f"(d[8]),"+f"(d[9]),"+f"(d[10]),"+f"(d[11]),"+f"(d[12]),"+f"(d[13]),"+f"(d[14]),"+f"(d[15]),"+f"(d[16]),"+f"(d[17]),"+f"(d[18]),"+f"(d[19]),"+f"(d[20]),"+f"(d[21]),"+f"(d[22]),"+f"(d[23]),"+f"(d[24]),"+f"(d[25]),"+f"(d[26]),"+f"(d[27]),"+f"(d[28]),"+f"(d[29]),"+f"(d[30]),"+f"(d[31]) : "r"(a[0]), "r"(a[1]), "r"(a[2]), "r"(a[3]), "l"(db), "n"(SD));
}
template<int SD> __device__ __forceinline__ void wgmma_rs_n96(float* d, const uint32_t* a, uint64_t db) {
    asm volatile("wgmma.mma_async.sync.aligned.m64n96k16.f32.bf16.bf16 {%0,%1,%2,%3,%4,%5,%6,%7,%8,%9,%10,%11,%12,%13,%14,%15,%16,%17,%18,%19,%20,%21,%22,%23,%24,%25,%26,%27,%28,%29,%30,%31,%32,%33,%34,%35,%36,%37,%38,%39,%40,%41,%42,%43,%44,%45,%46,%47}, {%48,%49,%50,%51}, %52, %53, 1, 1, 0;\n"
    : "+f"(d[0]),"+f"(d[1]),"+f"(d[2]),"+f"(d[3]),"+f"(d[4]),"+f"(d[5]),"+f"(d[6]),"+f"(d[7]),"+f"(d[8]),"+f"(d[9]),"+f"(d[10]),"+f"(d[11]),"+f"(d[12]),"+f"(d[13]),"+f"(d[14]),"+f"(d[15]),"+f"(d[16]),"+f"(d[17]),"+f"(d[18]),"+f"(d[19]),"+f"(d[20]),"+f"(d[21]),"+f"(d[22]),"+f"(d[23]),"+f"(d[24]),"+f"(d[25]),"+f"(d[26]),"+f"(d[27]),"+f"(d[28]),"+f"(d[29]),"+f"(d[30]),"+f"(d[31]),"+f"(d[32]),"+f"(d[33]),"+f"(d[34]),"+f"(d[35]),"+f"(d[36]),"+f"(d[37]),"+f"(d[38]),"+f"(d[39]),"+f"(d[40]),"+f"(d[41]),"+f"(d[42]),"+f"(d[43]),"+f"(d[44]),"+f"(d[45]),"+f"(d[46]),"+f"(d[47]) : "r"(a[0]), "r"(a[1]), "r"(a[2]), "r"(a[3]), "l"(db), "n"(SD));
}
template<int SD> __device__ __forceinline__ void wgmma_rs_n128(float* d, const uint32_t* a, uint64_t db) {
    asm volatile("wgmma.mma_async.sync.aligned.m64n128k16.f32.bf16.bf16 {%0,%1,%2,%3,%4,%5,%6,%7,%8,%9,%10,%11,%12,%13,%14,%15,%16,%17,%18,%19,%20,%21,%22,%23,%24,%25,%26,%27,%28,%29,%30,%31,%32,%33,%34,%35,%36,%37,%38,%39,%40,%41,%42,%43,%44,%45,%46,%47,%48,%49,%50,%51,%52,%53,%54,%55,%56,%57,%58,%59,%60,%61,%62,%63}, {%64,%65,%66,%67}, %68, %69, 1, 1, 0;\n"
    : "+f"(d[0]),"+f"(d[1]),"+f"(d[2]),"+f"(d[3]),"+f"(d[4]),"+f"(d[5]),"+f"(d[6]),"+f"(d[7]),"+f"(d[8]),"+f"(d[9]),"+f"(d[10]),"+f"(d[11]),"+f"(d[12]),"+f"(d[13]),"+f"(d[14]),"+f"(d[15]),"+f"(d[16]),"+f"(d[17]),"+f"(d[18]),"+f"(d[19]),"+f"(d[20]),"+f"(d[21]),"+f"(d[22]),"+f"(d[23]),"+f"(d[24]),"+f"(d[25]),"+f"(d[26]),"+f"(d[27]),"+f"(d[28]),"+f"(d[29]),"+f"(d[30]),"+f"(d[31]),"+f"(d[32]),"+f"(d[33]),"+f"(d[34]),"+f"(d[35]),"+f"(d[36]),"+f"(d[37]),"+f"(d[38]),"+f"(d[39]),"+f"(d[40]),"+f"(d[41]),"+f"(d[42]),"+f"(d[43]),"+f"(d[44]),"+f"(d[45]),"+f"(d[46]),"+f"(d[47]),"+f"(d[48]),"+f"(d[49]),"+f"(d[50]),"+f"(d[51]),"+f"(d[52]),"+f"(d[53]),"+f"(d[54]),"+f"(d[55]),"+f"(d[56]),"+f"(d[57]),"+f"(d[58]),"+f"(d[59]),"+f"(d[60]),"+f"(d[61]),"+f"(d[62]),"+f"(d[63]) : "r"(a[0]), "r"(a[1]), "r"(a[2]), "r"(a[3]), "l"(db), "n"(SD));
}
template<int N, int SD> __device__ __forceinline__ void wgmma_rs(float* d, const uint32_t* a, uint64_t db) {
    if constexpr (N == 16) wgmma_rs_n16<SD>(d, a, db);
    if constexpr (N == 32) wgmma_rs_n32<SD>(d, a, db);
    if constexpr (N == 48) wgmma_rs_n48<SD>(d, a, db);
    if constexpr (N == 64) wgmma_rs_n64<SD>(d, a, db);
    if constexpr (N == 96) wgmma_rs_n96<SD>(d, a, db);
    if constexpr (N == 128) wgmma_rs_n128<SD>(d, a, db);
}

__device__ __forceinline__ uint64_t make_desc(uint32_t saddr, uint32_t lbo, uint32_t sbo, uint32_t swz) {
    uint64_t d = 0;
    d |= (uint64_t)((saddr & 0x3FFFF) >> 4);
    d |= (uint64_t)((lbo & 0x3FFFF) >> 4) << 16;
    d |= (uint64_t)((sbo & 0x3FFFF) >> 4) << 32;
    d |= (uint64_t)swz << 62;
    return d;
}
#define WG_FENCE() asm volatile("wgmma.fence.sync.aligned;\n" ::: "memory")
#define WG_COMMIT() asm volatile("wgmma.commit_group.sync.aligned;\n" ::: "memory")
#define WG_WAIT(n) asm volatile("wgmma.wait_group.sync.aligned %0;\n" :: "n"(n) : "memory")
#define PP_SYNC() asm volatile("bar.sync %0, 256;" :: "r"(2 + cw) : "memory")
#define PP_ARRIVE() asm volatile("bar.arrive %0, 256;" :: "r"(3 - cw) : "memory")
#define FENCE_ASYNC_S() asm volatile("fence.proxy.async.shared::cta;\n" ::: "memory")
#define FENCE_ASYNC_G() asm volatile("fence.proxy.async.global;\n" ::: "memory")

__device__ __forceinline__ void mbar_init(uint32_t bar, uint32_t cnt) { asm volatile("mbarrier.init.shared::cta.b64 [%0], %1;" :: "r"(bar), "r"(cnt)); }
__device__ __forceinline__ void mbar_expect_tx(uint32_t bar, uint32_t bytes) { asm volatile("mbarrier.arrive.expect_tx.shared::cta.b64 _, [%0], %1;" :: "r"(bar), "r"(bytes) : "memory"); }
__device__ __forceinline__ void mbar_arrive(uint32_t bar) { asm volatile("mbarrier.arrive.shared::cta.b64 _, [%0];" :: "r"(bar) : "memory"); }
__device__ __forceinline__ bool mbar_try(uint32_t bar, uint32_t parity) {
    uint32_t ok;
    asm volatile("{\n.reg .pred p;\nmbarrier.try_wait.parity.shared::cta.b64 p, [%1], %2;\nselp.u32 %0, 1, 0, p;\n}\n" : "=r"(ok) : "r"(bar), "r"(parity) : "memory");
    return ok != 0;
}
__device__ __forceinline__ void mbar_wait(uint32_t bar, uint32_t parity) {
    if (mbar_try(bar, parity)) return;
    if (mbar_try(bar, parity)) return;
    long long t0 = clock64();
    while (!mbar_try(bar, parity)) { if (clock64() - t0 > 100000000LL) break; }
}
__device__ __forceinline__ void mbar_arrive_cluster(uint32_t bar, uint32_t cta) {
    asm volatile("{\n.reg .b32 ra;\nmapa.shared::cluster.u32 ra, %0, %1;\nmbarrier.arrive.shared::cluster.b64 _, [ra];\n}\n" :: "r"(bar), "r"(cta) : "memory");
}
__device__ __forceinline__ void tma2d(uint32_t dst, const CUtensorMap* tm, int c0, int c1, uint32_t bar) {
    asm volatile("cp.async.bulk.tensor.2d.shared::cluster.global.mbarrier::complete_tx::bytes [%0], [%1, {%3, %4}], [%2];"
        :: "r"(dst), "l"(tm), "r"(bar), "r"(c0), "r"(c1) : "memory");
}
__device__ __forceinline__ void tma2d_mc(uint32_t dst, const CUtensorMap* tm, int c0, int c1, uint32_t bar) {
    asm volatile("cp.async.bulk.tensor.2d.shared::cluster.global.mbarrier::complete_tx::bytes.multicast::cluster [%0], [%1, {%3, %4}], [%2], %5;"
        :: "r"(dst), "l"(tm), "r"(bar), "r"(c0), "r"(c1), "h"((uint16_t)3) : "memory");
}
__device__ __forceinline__ void bulk_load(uint32_t dst, const void* src, uint32_t bytes, uint32_t bar) {
    asm volatile("cp.async.bulk.shared::cluster.global.mbarrier::complete_tx::bytes [%0], [%1], %2, [%3];"
        :: "r"(dst), "l"(src), "r"(bytes), "r"(bar) : "memory");
}
__device__ __forceinline__ void tma3d_mc(uint32_t dst, const CUtensorMap* tm, int c1, int c2, uint32_t bar) {
    asm volatile("cp.async.bulk.tensor.3d.shared::cluster.global.mbarrier::complete_tx::bytes.multicast::cluster [%0], [%1, {%3, %4, %5}], [%2], %6;"
        :: "r"(dst), "l"(tm), "r"(bar), "r"(0), "r"(c1), "r"(c2), "h"((uint16_t)3) : "memory");
}
__device__ __forceinline__ void tma5d(uint32_t dst, const CUtensorMap* tm, int c0, int c4, uint32_t bar) {
    asm volatile("cp.async.bulk.tensor.5d.shared::cluster.global.mbarrier::complete_tx::bytes [%0], [%1, {%4, %3, %3, %3, %5}], [%2];"
        :: "r"(dst), "l"(tm), "r"(bar), "r"(0), "r"(c0), "r"(c4) : "memory");
}
__device__ __forceinline__ void l2_prefetch(const void* src, uint32_t bytes) {
    asm volatile("cp.async.bulk.prefetch.L2.global [%0], %1;" :: "l"(src), "r"(bytes) : "memory");
}
__device__ __forceinline__ void bulk_store(void* dst, uint32_t src, uint32_t bytes) {
    asm volatile("cp.async.bulk.global.shared::cta.bulk_group [%0], [%1], %2;" :: "l"(dst), "r"(src), "r"(bytes) : "memory");
}
__device__ __forceinline__ void tma2d_store(const CUtensorMap* tm, uint32_t src, int c0, int c1) {
    asm volatile("cp.async.bulk.tensor.2d.global.shared::cta.bulk_group [%0, {%2, %3}], [%1];" :: "l"(tm), "r"(src), "r"(c0), "r"(c1) : "memory");
}
__device__ __forceinline__ void cluster_sync_all() {
    asm volatile("barrier.cluster.arrive.relaxed;\nbarrier.cluster.wait;\n" ::: "memory");
}
__device__ __forceinline__ void wait_cnt(int idx, unsigned target) {
    const unsigned* p = &g_cnt[idx * 32];
    unsigned v;
    asm volatile("ld.relaxed.gpu.global.u32 %0, [%1];" : "=r"(v) : "l"(p) : "memory");
    if (v >= target) return;
    long long t0 = clock64();
    do {
        __nanosleep(40);
        asm volatile("ld.relaxed.gpu.global.u32 %0, [%1];" : "=r"(v) : "l"(p) : "memory");
        if (clock64() - t0 > 100000000LL) break;
    } while (v < target);
}
__device__ __forceinline__ void signal_cnt(int idx) {
    asm volatile("red.release.gpu.global.add.u32 [%0], 1;" :: "l"(&g_cnt[idx * 32]) : "memory");
}
__device__ __forceinline__ void signal_cnt_bulk(int idx) {
    asm volatile("red.relaxed.gpu.global.add.u32 [%0], 1;" :: "l"(&g_cnt[idx * 32]) : "memory");
}
__device__ __forceinline__ uint32_t pack2(float lo, float hi) {
    uint32_t r; asm("cvt.rn.bf16x2.f32 %0, %1, %2;" : "=r"(r) : "f"(hi), "f"(lo)); return r;
}
__device__ __forceinline__ uint32_t hmul2(uint32_t a, uint32_t b) { uint32_t r; asm("mul.rn.bf16x2 %0, %1, %2;" : "=r"(r) : "r"(a), "r"(b)); return r; }
__device__ __forceinline__ uint32_t hfma2(uint32_t a, uint32_t b, uint32_t c) { uint32_t r; asm("fma.rn.bf16x2 %0, %1, %2, %3;" : "=r"(r) : "r"(a), "r"(b), "r"(c)); return r; }
__device__ __forceinline__ float bf_lo(uint32_t v) { return __uint_as_float(v << 16); }
__device__ __forceinline__ float bf_hi(uint32_t v) { return __uint_as_float(v & 0xFFFF0000u); }
__device__ __forceinline__ float geglu(float g, float u) {
    float in = g * fmaf(g * g, 0.0356774081f, 0.7978845608f);
    float t; asm("tanh.approx.f32 %0, %1;" : "=f"(t) : "f"(in));
    float gu = g * u;
    return fmaf(gu, t, gu);
}
__device__ __forceinline__ uint32_t lds32(uint32_t a) { uint32_t v; asm volatile("ld.shared.u32 %0, [%1];" : "=r"(v) : "r"(a)); return v; }
__device__ __forceinline__ float lds_bf(uint32_t a) { uint16_t v; asm volatile("ld.shared.u16 %0, [%1];" : "=h"(v) : "r"(a)); return __uint_as_float((uint32_t)v << 16); }
__device__ __forceinline__ float2 lds64f(uint32_t a) { float2 v; asm volatile("ld.shared.v2.f32 {%0,%1}, [%2];" : "=f"(v.x), "=f"(v.y) : "r"(a)); return v; }
__device__ __forceinline__ void sts64f(uint32_t a, float x, float y) { asm volatile("st.shared.v2.f32 [%0], {%1,%2};" :: "r"(a), "f"(x), "f"(y) : "memory"); }
__device__ __forceinline__ void stsm4_t(uint32_t a, uint32_t r0, uint32_t r1, uint32_t r2, uint32_t r3) {
    asm volatile("stmatrix.sync.aligned.m8n8.x4.trans.shared.b16 [%0], {%1,%2,%3,%4};" :: "r"(a), "r"(r0), "r"(r1), "r"(r2), "r"(r3) : "memory");
}
__device__ __forceinline__ void stsm4(uint32_t a, uint32_t r0, uint32_t r1, uint32_t r2, uint32_t r3) {
    asm volatile("stmatrix.sync.aligned.m8n8.x4.shared.b16 [%0], {%1,%2,%3,%4};" :: "r"(a), "r"(r0), "r"(r1), "r"(r2), "r"(r3) : "memory");
}
__device__ __forceinline__ void ldsm4(uint32_t a, uint32_t* r) {
    asm volatile("ldmatrix.sync.aligned.m8n8.x4.shared.b16 {%0,%1,%2,%3}, [%4];" : "=r"(r[0]), "=r"(r[1]), "=r"(r[2]), "=r"(r[3]) : "r"(a) : "memory");
}
__device__ __forceinline__ void ldsm4_t(uint32_t a, uint32_t* r) {
    asm volatile("ldmatrix.sync.aligned.m8n8.x4.trans.shared.b16 {%0,%1,%2,%3}, [%4];" : "=r"(r[0]), "=r"(r[1]), "=r"(r[2]), "=r"(r[3]) : "r"(a) : "memory");
}

__device__ __forceinline__ void zero_pad(uint32_t cb, int j) {
    int off = j < 8 ? j * 16 : (j < 12 ? 4224 + (j - 8) * 16 : (j < 68 ? CB_P0 - 896 + (j - 12) * 16 : CB_P0 + CB_PS - 896 + (j - 68) * 16));
    asm volatile("st.shared.v4.u32 [%0], {%1,%1,%1,%1};" :: "r"(cb + off), "r"(0) : "memory");
}

struct Params {
    const bf16 *x, *k, *v, *shift_k, *ssm_k, *ssm_D, *gate_w, *wd, *wg, *wu;
};

template<int N, int SD> __device__ __forceinline__ void conv_group(float* acc, const uint32_t* a, uint64_t db0) {
    WG_FENCE();
    wgmma_rs<N, SD>(acc, a + 0, db0);
    wgmma_rs<N, 1>(acc, a + 4, db0 - 1);
    wgmma_rs<N, 1>(acc, a + 8, db0 - 4);
    wgmma_rs<N, 1>(acc, a + 12, db0 - 5);
    WG_COMMIT();
}
template<int NO> __device__ __forceinline__ void acc_widen(float* n, float* o) {
    #pragma unroll
    for (int j = 0; j < 8; j++) asm volatile("mov.b32 %0, 0;" : "=f"(n[j]) :: "memory");
    #pragma unroll
    for (int j = 0; j < NO; j++) asm volatile("add.f32 %0, %1, 0f00000000;" : "=f"(n[8 + j]) : "f"(o[j]) : "memory");
}
template<int N> __device__ __forceinline__ void acc_fence(float* o) {
    #pragma unroll
    for (int j = 0; j < N; j++) asm volatile("" : "+f"(o[j]) :: "memory");
}
__device__ __forceinline__ void conv_loadA(uint32_t* a, uint32_t addr) {
    #pragma unroll
    for (int s = 0; s < 4; s++) {
        uint32_t o = addr + ((s & 1) + (s >> 1) * 4) * 32;
        a[4 * s + 0] = lds32(o);
        a[4 * s + 1] = lds32(o + 256);
        a[4 * s + 2] = lds32(o + 16);
        a[4 * s + 3] = lds32(o + 272);
    }
}
#define AFENCE(a) _Pragma("unroll") for (int _i = 0; _i < 16; _i++) asm volatile("" : "+r"(a[_i]) :: "memory")

__global__ void __cluster_dims__(2, 1, 1) __launch_bounds__(512, 1)
fused_kernel(const __grid_constant__ CUtensorMap tmX, const __grid_constant__ CUtensorMap tmWg, const __grid_constant__ CUtensorMap tmWu,
             const __grid_constant__ CUtensorMap tmWg2, const __grid_constant__ CUtensorMap tmWu2, const __grid_constant__ CUtensorMap tmWd,
             const __grid_constant__ CUtensorMap tmK, const __grid_constant__ CUtensorMap tmQ,
             const __grid_constant__ CUtensorMap tmZ, const __grid_constant__ CUtensorMap tmO,
             const Params prm) {
    extern __shared__ __align__(1024) uint8_t smem_raw[];
    const uint32_t sb = (uint32_t)__cvta_generic_to_shared(smem_raw);
    const uint32_t bars = sb + OFF_BAR;
    const int tid = threadIdx.x, wg = tid >> 7, warp = tid >> 5, lane = tid & 31;
    const int bid = blockIdx.x, rank = bid & 1, cl = bid >> 1;
    const int m1 = 2 * (cl & 7) + rank, role = cl >> 3;
    const int m2 = cl & 15, n2 = 2 * (cl >> 4) + rank;
    if (tid == 0) {
        for (int i = 0; i < NST1; i++) { mbar_init(bars + (B_FULL1 + i) * 8, 1); mbar_init(bars + (B_EMPTY1 + i) * 8, 4); }
        for (int i = 0; i < NST2; i++) { mbar_init(bars + (B_FULL2 + i) * 8, 1); mbar_init(bars + (B_EMPTY2 + i) * 8, 2); }
        mbar_init(bars + B_QF * 8, 1); mbar_init(bars + B_ZF * 8, 1); mbar_init(bars + B_XFREE * 8, 2);
        for (int i = 0; i < 2; i++) { mbar_init(bars + (B_XF + i) * 8, 1); mbar_expect_tx(bars + (B_XF + i) * 8, 20480); }
        for (int i = 0; i < 2; i++) { mbar_init(bars + (B_CFULL + i) * 8, 2); mbar_init(bars + (B_CDONE + i) * 8, 4); mbar_init(bars + (B_CRAW + i) * 8, 1); }
        mbar_init(bars + B_HD * 8, 8); mbar_init(bars + B_WD * 8, 1); mbar_init(bars + B_KIN * 8, 1); mbar_init(bars + B_PRE * 8, 4); mbar_init(bars + B_STG * 8, 1); mbar_init(bars + B_KV * 8, 4); mbar_init(bars + B_KV1 * 8, 4); mbar_init(bars + B_G * 8, 1);
        asm volatile("fence.mbarrier_init.release.cluster;" ::: "memory");
    }
    if (tid >= 384 && tid < 396) zero_pad(sb + OFF_CB, tid - 384);
    __syncthreads();
    cluster_sync_all();

    if (wg == 0) {
        asm volatile("setmaxnreg.dec.sync.aligned.u32 24;\n");
        if (warp == 0 && lane == 0) {
            const CUtensorMap* tw = rank == 0 ? &tmWg : &tmWu;
            PROF(29);
            for (int it = 0; it < 20; it++) {
                int st = it & 3;
                mbar_wait(bars + (B_EMPTY1 + st) * 8, ((it >> 2) & 1) ^ 1);
                uint32_t full = bars + (B_FULL1 + st) * 8;
                uint32_t sa = sb + st * ST1;
                if (it < 10) {
                    mbar_expect_tx(full, ST1);
                    tma2d_mc(sa + 16384 + rank * 16384, tw, role * 128, it * 64, full);
                    tma2d_mc(sa + 24576 + rank * 16384, tw, role * 128 + 64, it * 64, full);
                    tma2d(sa, &tmX, it * 64, m1 * 128, full);
                } else {
                    int kb = it < 14 ? it - 4 : it - 14;
                    mbar_expect_tx(full, it < 14 ? 24576 : 40960);
                    tma3d_mc(sa + 16384 + rank * 12288, rank == 0 ? &tmWg2 : &tmWu2, kb * 64, 32 + 3 * role, full);
                    if (it >= 14) tma2d(sa, &tmX, kb * 64, m1 * 128, full);
                    if (it < 13 && bid < 120) {
                        if (it == 10) mbar_expect_tx(bars + B_WD * 8, 9 * 2048);
                        for (int q = 0; q < 3; q++) {
                            int pi = bid * 9 + (it - 10) * 3 + q, img = pi / 10, np = img / 27;
                            tma5d(sa + 40960 + q * 2048, &tmWd, np * 160 + (pi - img * 10) * 16, (img - np * 27) * 2, bars + B_WD * 8);
                        }
                    }
                }
            }
            wait_cnt(C_W, 120);
            wait_cnt(C_H1 + m2, 8);
            FENCE_ASYNC_G();
            PROF(8);
            int st = 0; uint32_t ph = 1;
            for (int it = 0; it < 14; it++) {
                if (it != 4) {
                    if (it < 5) mbar_wait(bars + (B_EMPTY1 + (it < 3 ? it : it - 1)) * 8, 0);
                    else mbar_wait(bars + (B_EMPTY2 + st) * 8, ph);
                    uint32_t full = bars + (B_FULL2 + st) * 8;
                    uint32_t sa = sb + st * ST2;
                    int kb = it < 13 ? 2 * it + rank : 26;
                    mbar_expect_tx(full, it < 13 ? ST2 : 26624);
                    bulk_load(sa + 16384, g_wd + ((cl >> 4) * 27 + kb) * 10240 + (it < 13 ? 0 : rank * 5120), it < 13 ? 20480 : 10240, full);
                    if (it < 8) bulk_load(sa, g_h + (m2 * 27 + kb) * 8192, 16384, full);
                }
                if (++st == NST2) { st = 0; ph ^= 1; }
            }
            mbar_wait(bars + (B_EMPTY2 + 4) * 8, 1);
            mbar_expect_tx(bars + B_QF * 8, 20480 + 16384);
            tma2d(sb + OFF_Q, &tmQ, n2 * 80, m2 * 128, bars + B_QF * 8);
            PROF(10);
            wait_cnt(C_Z + n2, 64);
            FENCE_ASYNC_G();
            for (int i = 0; i < 8; i++) tma2d(sb + OFF_Z + (i & 1) * 10240 + (i >> 1) * 2048, &tmZ, m2 * 128 + (i & 1) * 64, n2 * 80 + (i >> 1) * 16, bars + B_QF * 8);
            wait_cnt(C_ZL + n2, 16);
            FENCE_ASYNC_G();
            PROF(11);
            mbar_expect_tx(bars + B_ZF * 8, 4096);
            tma2d(sb + OFF_Z + 8192, &tmZ, m2 * 128, n2 * 80 + 64, bars + B_ZF * 8);
            tma2d(sb + OFF_Z + 10240 + 8192, &tmZ, m2 * 128 + 64, n2 * 80 + 64, bars + B_ZF * 8);
            if (atomicAdd(&g_cnt[C_DONE * 32], 1u) == 127u) {
                for (int i = 0; i < C_NUM; i++) g_cnt[i * 32] = 0;
            }
        } else if (warp == 1 && lane == 0) {
            const int ch0 = (bid >> 4) * 80 + (bid & 15);
            auto load_h = [&](int i) {
                uint32_t cb = sb + OFF_CB + (i & 1) * CB, full = bars + (B_CRAW + (i & 1)) * 8;
                mbar_expect_tx(full, 4096);
                bulk_load(cb + CB_HA, prm.ssm_k + (ch0 + 16 * i) * SEQ, 4096, full);
            };
            auto load_x = [&](int i) {
                uint32_t cb = sb + OFF_CB + (i & 1) * CB, full = bars + (B_CFULL + (i & 1)) * 8;
                mbar_expect_tx(full, 4096);
                bulk_load(cb + CB_P0, g_kvT + (ch0 + 16 * i) * SEQ, 2048, full);
                bulk_load(cb + CB_P0 + CB_PS, g_kvT + (ch0 + 16 * i) * SEQ + 1024, 2048, full);
            };
            mbar_wait(bars + (B_FULL1 + KV_WAIT) * 8, 0);
            mbar_expect_tx(bars + B_KIN * 8, 131 * 160 + 640);
            tma2d(sb + OFF_KT, &tmK, role * 80, m1 * 128 - 3, bars + B_KIN * 8);
            bulk_load(sb + OFF_SK, prm.shift_k + role * 320, 640, bars + B_KIN * 8);
            load_h(0);
            l2_prefetch(prm.gate_w, 1280);
            wait_cnt(C_KV0 + (bid >> 4), 16);
            FENCE_ASYNC_G();
            load_x(0);
            mbar_wait(bars + B_PRE * 8, 0);
            load_h(1);
            wait_cnt(C_KV + (bid >> 4), 16);
            FENCE_ASYNC_G();
            load_x(1);
            for (int i = 0; i < NCH; i++) {
                mbar_wait(bars + (B_CDONE + (i & 1)) * 8, (i >> 1) & 1);
                bulk_store(g_zT + (ch0 + 16 * i) * SEQ, sb + OFF_STG, 4096);
                asm volatile("cp.async.bulk.commit_group;" ::: "memory");
                if (i + 2 < NCH) { load_h(i + 2); load_x(i + 2); }
                asm volatile("cp.async.bulk.wait_group.read 0;" ::: "memory");
                mbar_arrive(bars + B_STG * 8);
                asm volatile("cp.async.bulk.wait_group 0;" ::: "memory");
                FENCE_ASYNC_G();
                signal_cnt_bulk((i < NCH - 1 ? C_Z : C_ZL) + (bid >> 4));
            }
            PROF(12);
        } else if (warp == 2) {
#define PF_WAIT 8
            if (lane == 0 && PF_WAIT < 8) {
                mbar_wait(bars + (B_FULL1 + (PF_WAIT & 3)) * 8, 0);
                if (PF_WAIT >= 4) mbar_wait(bars + (B_FULL1 + (PF_WAIT & 3)) * 8, 1);
                l2_prefetch(prm.wg + bid * 5 * DF, 5 * DF * 2);
                l2_prefetch(prm.wu + bid * 5 * DF, 5 * DF * 2);
                l2_prefetch(prm.x + bid * 16 * DM, 16 * DM * 2);
                l2_prefetch(prm.wd + bid * 8640, 17280);
                l2_prefetch(prm.ssm_k + bid * 5 * SEQ, 5 * SEQ * 2);
            }
            __syncwarp();
            for (int i = 0; i < NCH; i++) {
                const uint32_t cb = sb + OFF_CB + (i & 1) * CB + lane * 16;
                mbar_wait(bars + (B_CRAW + (i & 1)) * 8, (i >> 1) & 1);
                #pragma unroll
                for (int j = 0; j < 8; j++) {
                    uint32_t x0, x1, x2, x3, pv = lds32(cb + CB_HA + j * 512 - 4);
                    asm volatile("ld.shared.v4.u32 {%0,%1,%2,%3}, [%4];" : "=r"(x0), "=r"(x1), "=r"(x2), "=r"(x3) : "r"(cb + CB_HA + j * 512));
                    asm volatile("st.shared.v4.u32 [%0], {%1,%2,%3,%4};" :: "r"(cb + CB_HB + j * 512), "r"(__byte_perm(pv, x0, 0x5432)), "r"(__byte_perm(x0, x1, 0x5432)),
                                 "r"(__byte_perm(x1, x2, 0x5432)), "r"(__byte_perm(x2, x3, 0x5432)) : "memory");
                }
                __syncwarp();
                if (lane == 0) mbar_arrive(bars + (B_CFULL + (i & 1)) * 8);
            }
        } else if (warp == 3 && lane == 0) {
            mbar_wait(bars + B_KV * 8, 0);
            signal_cnt(C_KV0 + role);
            PROF(23);
            mbar_wait(bars + B_KV1 * 8, 0);
            signal_cnt(C_KV + role);
            PROF(14);
            mbar_wait(bars + B_HD * 8, 0);
            signal_cnt(C_H1 + m1);
            if (bid < 120) {
                mbar_wait(bars + B_WD * 8, 0);
                for (int q = 0; q < 3; q++) bulk_store(g_wd + (bid * 9 + q * 3) * 1024, sb + ((2 + q) & 3) * ST1 + 40960, 6144);
                asm volatile("cp.async.bulk.commit_group;" ::: "memory");
                asm volatile("cp.async.bulk.wait_group 0;" ::: "memory");
                FENCE_ASYNC_G();
                signal_cnt_bulk(C_W);
            }
            PROF(15);
            wait_cnt(C_W, 120);
            wait_cnt(C_H1 + m2, 8);
            FENCE_ASYNC_G();
            mbar_wait(bars + B_HD * 8, 1);
            bulk_store(g_h + (m1 * 54 + 32 + 3 * role) * 4096, sb + OFF_HS, role < 7 ? 24576 : 8192);
            bulk_store(g_gate + m1 * 128 + role * 16, sb + OFF_HS + 24576, 64);
            asm volatile("cp.async.bulk.commit_group;" ::: "memory");
            asm volatile("cp.async.bulk.wait_group.read 0;" ::: "memory");
            mbar_expect_tx(bars + (B_FULL2 + 4) * 8, ST2);
            bulk_load(sb + 4 * ST2 + 16384, g_wd + ((cl >> 4) * 27 + 8 + rank) * 10240, 20480, bars + (B_FULL2 + 4) * 8);
            bulk_load(sb + 4 * ST2, g_h + (m2 * 27 + 8 + rank) * 8192, 16384, bars + (B_FULL2 + 4) * 8);
            asm volatile("cp.async.bulk.wait_group 0;" ::: "memory");
            FENCE_ASYNC_G();
            signal_cnt_bulk(C_H2 + m1);
            wait_cnt(C_H2 + m2, 8);
            FENCE_ASYNC_G();
            PROF(9);
            for (int it = 8; it < 14; it++) {
                int st = it < 10 ? it - 5 : it - 10;
                mbar_wait(bars + (B_EMPTY2 + st) * 8, it < 10 ? 0 : 1);
                bulk_load(sb + st * ST2, g_h + (m2 * 27 + (it < 13 ? 2 * it + rank : 26)) * 8192, 16384, bars + (B_FULL2 + st) * 8);
            }
        }
        if (tid == 0) { PROF(13); }
    } else if (wg == 3) {
        asm volatile("setmaxnreg.inc.sync.aligned.u32 168;\n");
        const int t = tid - 384, w = warp & 3;
        const float Dall = lane < NCH ? __bfloat162float(prm.ssm_D[(bid >> 4) * 80 + (bid & 15) + 16 * lane]) : 0.f;
        {
            const int r = lane >> 2, c = lane & 3;
            const int tb = 64 * (w >> 1) + 16 * (r >> 1) + 15 - 8 * (w & 1) - (r & 1);
            const bf16* vp = prm.v + (m1 * 128 + tb) * DM + role * 80 + c * 4;
            uint2 vv[5][4];
            #pragma unroll
            for (int g = 0; g < 5; g++)
                #pragma unroll
                for (int b = 0; b < 4; b++) vv[g][b] = __ldg((const uint2*)(vp - 2 * b * DM + g * 16));
            bf16* dst = g_kvT + (role * 80 + 4 * (r >> 1) + (r & 1)) * SEQ + (w & 1) * 1024 + (m1 * 8 + 4 * (w >> 1) + c) * 8;
            const uint32_t ka = sb + OFF_KT + (tb + 3) * 160 + c * 8, wa = sb + OFF_SK + c * 32;
            uint4 sw[2][2];
            uint2 kb[2][10];
            mbar_wait(bars + B_KIN * 8, 0);

            #pragma unroll
            for (int g = -1; g < 5; g++) {
                if (g < 4) {
                    #pragma unroll
                    for (int m = 0; m < 10; m++) asm volatile("ld.shared.v2.u32 {%0,%1}, [%2];" : "=r"(kb[(g + 1) & 1][m].x), "=r"(kb[(g + 1) & 1][m].y) : "r"(ka + (g + 1) * 32 - m * 160));
                    #pragma unroll
                    for (int j = 0; j < 2; j++) asm volatile("ld.shared.v4.u32 {%0,%1,%2,%3}, [%4];" : "=r"(sw[(g + 1) & 1][j].x), "=r"(sw[(g + 1) & 1][j].y), "=r"(sw[(g + 1) & 1][j].z), "=r"(sw[(g + 1) & 1][j].w) : "r"(wa + (g + 1) * 128 + j * 16));
                }
                if (g < 0) continue;
                const uint2* kk = kb[g & 1];
                #pragma unroll
                for (int j = 0; j < 2; j++) {
                    uint32_t s0 = sw[g & 1][j].x, s1 = sw[g & 1][j].y, s2 = sw[g & 1][j].z, s3 = sw[g & 1][j].w, o[4];
                    const uint32_t w0 = __byte_perm(s0, s2, 0x5410), w1 = __byte_perm(s0, s2, 0x7632), w2 = __byte_perm(s1, s3, 0x5410), w3 = __byte_perm(s1, s3, 0x7632);
                    #pragma unroll
                    for (int b = 0; b < 4; b++) {
                        uint32_t a = hmul2(j ? kk[2 * b + 3].y : kk[2 * b + 3].x, w3);
                        a = hfma2(j ? kk[2 * b + 2].y : kk[2 * b + 2].x, w2, a);
                        a = hfma2(j ? kk[2 * b + 1].y : kk[2 * b + 1].x, w1, a);
                        a = hfma2(j ? kk[2 * b].y : kk[2 * b].x, w0, a);
                        a = hmul2(a, j ? vv[g][b].y : vv[g][b].x);
                        asm volatile("movmatrix.sync.aligned.m8n8.trans.b16 %0, %1;" : "=r"(o[b]) : "r"(a));
                    }
                    *(uint4*)(dst + (g * 16 + 2 * j) * SEQ) = make_uint4(o[0], o[1], o[2], o[3]);
                }
                if (g == 0 || g == 4) { __syncwarp(); if (lane == 0) mbar_arrive(bars + (g ? B_KV1 : B_KV) * 8); }

            }
            asm volatile("bar.sync 1, 128;" ::: "memory");

            if (t < 124) { zero_pad(sb + OFF_CB, t); zero_pad(sb + OFF_CB + CB, t); }
            FENCE_ASYNC_S();
            if (t == 127) { mbar_expect_tx(bars + B_G * 8, 1280); bulk_load(sb + OFF_GW, prm.gate_w, 1280, bars + B_G * 8); }
            __syncwarp();
            if (lane == 0) mbar_arrive(bars + B_PRE * 8);
            mbar_wait(bars + B_PRE * 8, 0);
        }

        const int w0 = w & 1, w1 = w >> 1, r = lane >> 2, c = lane & 3;
        const uint32_t a_off = (r & 1) ? CB_HA + 2 * (32 * w1 + 8 * w0 + r - 15 + 2 * c) : CB_HB + 2 * (32 * w1 + 8 * w0 + r - 14 + 2 * c);
        const uint32_t stg = sb + OFF_STG;
        for (int i = 0; i < NCH; i++) {
            const uint32_t cb = sb + OFF_CB + (i & 1) * CB;
            const float Dv = __shfl_sync(0xffffffffu, Dall, i);
            mbar_wait(bars + (B_CFULL + (i & 1)) * 8, (i >> 1) & 1);
            if (t == 0) { PROF(16 + i); }
            float acc[64], t96[48], t64[32], t48[24], t32[16], t16[8];
            uint32_t a0[16], a1[16], a2[16];
            const uint64_t db0 = make_desc(cb + CB_P0, CB_PS, 128, 0);
            const uint32_t aa = cb + a_off;
            conv_loadA(a0, aa + 7 * 512);
            conv_loadA(a1, aa + 6 * 512);
            conv_loadA(a2, aa + 5 * 512);
            conv_group<16, 0>(t16, a0, db0);
            conv_group<32, 0>(t32, a1, db0);
            WG_WAIT(1); AFENCE(a0); conv_loadA(a0, aa + 4 * 512);
            conv_group<48, 0>(t48, a2, db0);
            WG_WAIT(1); AFENCE(a1); conv_loadA(a1, aa + 3 * 512);
            conv_group<64, 0>(t64, a0, db0);
            acc_fence<8>(t16); acc_fence<16>(t32);
            #pragma unroll
            for (int j = 0; j < 8; j++) t32[8 + j] += t16[j];
            WG_WAIT(1); AFENCE(a2); conv_loadA(a2, aa + 2 * 512);
            acc_fence<24>(t48);
            #pragma unroll
            for (int j = 0; j < 16; j++) t48[8 + j] += t32[j];
            WG_WAIT(0); AFENCE(a0);
            #pragma unroll
            for (int j = 0; j < 32; j++) asm volatile("add.f32 %0, %1, %2;" : "=f"(t96[16 + j]) : "f"(t64[j]), "f"(j < 8 ? 0.f : t48[j < 8 ? 0 : j - 8]) : "memory");
            #pragma unroll
            for (int j = 0; j < 16; j++) asm volatile("mov.b32 %0, 0;" : "=f"(t96[j]) :: "memory");
            conv_group<96, 1>(t96, a1, db0 - 16);
            conv_loadA(a0, aa + 1 * 512);
            conv_group<96, 1>(t96, a2, db0);
            WG_WAIT(1); AFENCE(a1); conv_loadA(a1, aa);
            WG_WAIT(0); AFENCE(a2);
            #pragma unroll
            for (int j = 0; j < 48; j++) asm volatile("add.f32 %0, %1, 0f00000000;" : "=f"(acc[16 + j]) : "f"(t96[j]) : "memory");
            #pragma unroll
            for (int j = 0; j < 16; j++) asm volatile("mov.b32 %0, 0;" : "=f"(acc[j]) :: "memory");
            conv_group<128, 1>(acc, a0, db0 - 16);
            conv_group<128, 1>(acc, a1, db0);
            WG_WAIT(0);
            AFENCE(a0); AFENCE(a1);
            acc_fence<64>(acc);
            if (t == 0 && i == CI) { PROF(26); }
            #pragma unroll
            for (int q = 15; q >= 1; q--) { acc[4 * q] += acc[4 * q - 2]; acc[4 * q + 1] += acc[4 * q - 1]; }
            asm volatile("bar.sync 1, 128;" ::: "memory");
            const uint32_t xs1 = cb + CB_HA + w0 * 2048, xs0 = cb + CB_HB + w0 * 2048;
            if (w1 == 0) {
                #pragma unroll
                for (int q = 8; q < 16; q++) sts64f(xs0 + (q - 8) * 256 + lane * 8, acc[4 * q], acc[4 * q + 1]);
            } else {
                #pragma unroll
                for (int q = 0; q < 8; q++) sts64f(xs1 + q * 256 + lane * 8, acc[4 * q], acc[4 * q + 1]);
            }
            if (i > 0) mbar_wait(bars + B_STG * 8, (i - 1) & 1);
            asm volatile("bar.sync 1, 128;" ::: "memory");
            if (t == 0 && i == CI) { PROF(27); }
            const uint32_t kvp = cb + CB_P0 + (1 - w0) * CB_PS + (7 - r) * 2 + c * 32;
            uint32_t pk[8];
            if (w1 == 0) {
                const uint32_t rd = xs1 + (c > 0 ? lane * 8 - 8 : lane * 8 + 24 - 256);
                #pragma unroll
                for (int q = 0; q < 9; q++) {
                    float2 o = make_float2(0.f, 0.f);
                    if (q == 0) { if (c > 0) o = lds64f(rd); }
                    else if (q == 8) { if (c == 0) o = lds64f(rd + q * 256); }
                    else o = lds64f(rd + q * 256);
                    float z0 = fmaf(Dv, lds_bf(kvp + q * 128), acc[4 * q] + o.x);
                    float z1 = fmaf(Dv, lds_bf(kvp + q * 128 + 16), acc[4 * q + 1] + o.y);
                    uint32_t pz = pack2(z0, z1);
                    if (q < 8) pk[q] = pz;
                    else if (c == 0) {
                        asm volatile("st.shared.u16 [%0], %1;" :: "r"(stg + 64 * 32 + w0 * 16 + r * 2), "h"((uint16_t)(pz & 0xFFFF)) : "memory");
                        asm volatile("st.shared.u16 [%0], %1;" :: "r"(stg + 65 * 32 + w0 * 16 + r * 2), "h"((uint16_t)(pz >> 16)) : "memory");
                    }
                }
                stsm4_t(stg + lane * 32 + w0 * 16, pk[0], pk[1], pk[2], pk[3]);
                stsm4_t(stg + (32 + lane) * 32 + w0 * 16, pk[4], pk[5], pk[6], pk[7]);
            } else {
                const uint32_t rd = xs0 + (c < 3 ? lane * 8 + 8 : lane * 8 - 24 + 256);
                #pragma unroll
                for (int q = 8; q < 16; q++) {
                    float2 o = make_float2(0.f, 0.f);
                    float k0 = 0.f, k1 = 0.f;
                    if (q < 15 || c < 3) { o = lds64f(rd + (q - 8) * 256); k0 = lds_bf(kvp + q * 128 + 32); k1 = lds_bf(kvp + q * 128 + 48); }
                    pk[q - 8] = pack2(fmaf(Dv, k0, acc[4 * q] + o.x), fmaf(Dv, k1, acc[4 * q + 1] + o.y));
                }
                stsm4_t(stg + (66 + lane) * 32 + w0 * 16, pk[0], pk[1], pk[2], pk[3]);
                stsm4_t(stg + (98 + lane) * 32 + w0 * 16, pk[4], pk[5], pk[6], pk[7]);
            }
            FENCE_ASYNC_S();
            __syncwarp();
            if (lane == 0) mbar_arrive(bars + (B_CDONE + (i & 1)) * 8);
            if (t == 0 && i == CI) { PROF(28); }
        }
        if (t == 0) { PROF(21); }
    } else {
        asm volatile("setmaxnreg.inc.sync.aligned.u32 160;\n");
        const int cw = wg - 1, t = tid & 127, w = warp & 3, r = lane >> 2, c = lane & 3;
        {
            float d[128];
            if (cw == 1) PP_ARRIVE();
            for (int it = 0; it < 10; it++) {
                int st = it & 3;
                mbar_wait(bars + (B_FULL1 + st) * 8, (it >> 2) & 1);
                if (it == 0 && tid == 128) { PROF(0); }
                uint64_t da = make_desc(sb + st * ST1 + cw * 8192, 16, 1024, 1);
                uint64_t db = make_desc(sb + st * ST1 + 16384, 8192, 1024, 1);
                PP_SYNC();
                WG_FENCE();
                #pragma unroll
                for (int k = 0; k < 4; k++) {
                    wgmma_ss_n128(d, da + k * 2, db + k * 128, (it | k) != 0);
                    wgmma_ss_n128(d + 64, da + k * 2, db + 1024 + k * 128, (it | k) != 0);
                }
                WG_COMMIT();
                PP_ARRIVE();
                WG_WAIT(0);
                if (t < 2) mbar_arrive_cluster(bars + (B_EMPTY1 + st) * 8, t);
            }
            WG_WAIT(0);
            #pragma unroll
            for (int j = 0; j < 128; j++) asm volatile("" : "+f"(d[j]) :: "memory");
            if (tid == 128) { PROF(1); }
            bf16* hrow = g_h + (m1 * 54 + role * 4) * 4096 + cw * 2048 + w * 512 + c * 64 + r * 8;
            #pragma unroll
            for (int G = 0; G < 4; G++) {
                #pragma unroll
                for (int hf = 0; hf < 2; hf++) {
                    uint32_t p[4];
                    #pragma unroll
                    for (int q = 0; q < 4; q++) {
                        int j = (G * 4 + q) * 4 + hf * 2;
                        p[q] = pack2(geglu(d[j], d[64 + j]), geglu(d[j + 1], d[64 + j + 1]));
                    }
                    *(uint4*)(hrow + hf * 256 + G * 4096) = make_uint4(p[0], p[1], p[2], p[3]);
                }
            }
            __syncwarp();
            if (lane == 0) mbar_arrive(bars + B_HD * 8);
            if (tid == 128) { PROF(2); }
            float d2[96];
            const int grow = role * 16 + (warp - 4) * 2 + (lane >> 4);
            const uint32_t gx = sb + grow * 128 + ((((lane >> 1) & 7) ^ (grow & 7)) << 4) + (lane & 1) * 8;
            const uint32_t gwp = sb + OFF_GW + (lane & 15) * 8;
            mbar_wait(bars + B_G * 8, 0);
            float gs = 0.f;
            for (int it = 10; it < 20; it++) {
                int st = it & 3;
                mbar_wait(bars + (B_FULL1 + st) * 8, (it >> 2) & 1);
                uint64_t da = make_desc(sb + st * ST1 + cw * 8192, 16, 1024, 1);
                uint64_t db = make_desc(sb + st * ST1 + 16384, 4096, 512, 2);
                PP_SYNC();
                WG_FENCE();
                #pragma unroll
                for (int k = 0; k < 4; k++) {
                    wgmma_ss_n192(d2, da + k * 2, db + k * 64, ((it - 10) | k) != 0);
                }
                WG_COMMIT();
                PP_ARRIVE();
                uint32_t x0, x1; uint2 gwv;
                asm volatile("ld.shared.v2.u32 {%0,%1}, [%2];" : "=r"(gwv.x), "=r"(gwv.y) : "r"(gwp + (it < 14 ? it - 4 : it - 14) * 128));
                asm volatile("ld.shared.v2.u32 {%0,%1}, [%2];" : "=r"(x0), "=r"(x1) : "r"(gx + st * ST1));
                gs = fmaf(bf_lo(x0), bf_lo(gwv.x), fmaf(bf_hi(x0), bf_hi(gwv.x), fmaf(bf_lo(x1), bf_lo(gwv.y), fmaf(bf_hi(x1), bf_hi(gwv.y), gs))));
                asm volatile("bar.sync %0, 128;" :: "r"(4 + cw), "f"(gs) : "memory");
                WG_WAIT(0);
                if (t < 2) mbar_arrive_cluster(bars + (B_EMPTY1 + st) * 8, t);
            }
            #pragma unroll
            for (int o = 1; o < 16; o <<= 1) gs += __shfl_xor_sync(0xffffffffu, gs, o);
            WG_WAIT(0);
            asm volatile("bar.sync 6, 256;" ::: "memory");
            if ((lane & 15) == 0) asm volatile("st.shared.f32 [%0], %1;" :: "r"(sb + OFF_HS + 24576 + (grow & 15) * 4), "f"(1.0f / (1.0f + __expf(-gs))) : "memory");
            #pragma unroll
            for (int j = 0; j < 96; j++) asm volatile("" : "+f"(d2[j]) :: "memory");
            if (tid == 128) { PROF(3); }
            #pragma unroll
            for (int G = 0; G < 3; G++) {
                int Gg = 32 + role * 3 + G;
                if (Gg < DF / 32) {
                    #pragma unroll
                    for (int hf = 0; hf < 2; hf++) {
                        uint32_t p[4];
                        #pragma unroll
                        for (int q = 0; q < 4; q++) {
                            int j = (G * 4 + q) * 4 + hf * 2;
                            p[q] = pack2(geglu(d2[j], d2[48 + j]), geglu(d2[j + 1], d2[48 + j + 1]));
                        }
                        asm volatile("st.shared.v4.u32 [%0], {%1,%2,%3,%4};" :: "r"(sb + OFF_HS + G * 8192 + cw * 4096 + w * 1024 + hf * 512 + c * 128 + r * 16), "r"(p[0]), "r"(p[1]), "r"(p[2]), "r"(p[3]) : "memory");
                    }
                }
            }
            FENCE_ASYNC_S();
            __syncwarp();
            if (lane == 0) mbar_arrive(bars + B_HD * 8);
            if (tid == 128) { PROF(4); }
        }
        float e[40], g0, g1;
        {
            float f[80];
            int st = 0; uint32_t ph = 0;
            for (int it = 0; it < 13; it++) {
                mbar_wait(bars + (B_FULL2 + st) * 8, ph);
                uint64_t da = make_desc(sb + st * ST2 + cw * 4096, 128, 512, 0);
                uint64_t db = make_desc(sb + st * ST2 + 16384, 2048, 256, 3);
                PP_SYNC();
                WG_FENCE();
                #pragma unroll
                for (int k = 0; k < 4; k++) wgmma_ss_n160(f, da + (k & 1) * 16 + (k >> 1) * 512, db + k * 32, (it | k) != 0);
                WG_COMMIT();
                if (cw == 0 || it < 12) PP_ARRIVE();
                WG_WAIT(0);
                if (t == 0) mbar_arrive(bars + (B_EMPTY2 + st) * 8);
                if (it == 11 && t == 32) mbar_arrive_cluster(bars + B_XFREE * 8, rank ^ 1);
                if (++st == NST2) { st = 0; ph ^= 1; }
            }
            WG_WAIT(0);
            #pragma unroll
            for (int j = 0; j < 80; j++) asm volatile("" : "+f"(f[j]) :: "memory");
            if (tid == 128) { PROF(5); }
            asm volatile("ld.global.cg.f32 %0, [%1];" : "=f"(g0) : "l"(&g_gate[m2 * 128 + cw * 64 + w * 16 + r]) : "memory");
            asm volatile("ld.global.cg.f32 %0, [%1];" : "=f"(g1) : "l"(&g_gate[m2 * 128 + cw * 64 + w * 16 + r + 8]) : "memory");
            uint32_t xa = sb + cw * 20480 + t * 16, xb = bars + (B_XF + cw) * 8, ra, rb;
            asm volatile("mapa.shared::cluster.u32 %0, %1, %2;" : "=r"(ra) : "r"(xa), "r"(rank ^ 1));
            asm volatile("mapa.shared::cluster.u32 %0, %1, %2;" : "=r"(rb) : "r"(xb), "r"(rank ^ 1));
            #pragma unroll
            for (int j = 0; j < 40; j++) e[j] = rank ? f[40 + j] : f[j];
            mbar_wait(bars + (B_FULL2 + 3) * 8, 0);
            {
                uint64_t da = make_desc(sb + 3 * ST2 + cw * 4096, 128, 512, 0);
                uint64_t db = make_desc(sb + 3 * ST2 + 16384, 2048, 256, 3);
                WG_FENCE();
                #pragma unroll
                for (int k = 0; k < 4; k++) wgmma_ss_n80(e, da + (k & 1) * 16 + (k >> 1) * 512, db + k * 32, 1);
                WG_COMMIT();
            }
            mbar_wait(bars + B_XFREE * 8, 0);
            #pragma unroll
            for (int j = 0; j < 10; j++) {
                float s0 = rank ? f[4 * j] : f[40 + 4 * j], s1 = rank ? f[4 * j + 1] : f[41 + 4 * j], s2 = rank ? f[4 * j + 2] : f[42 + 4 * j], s3 = rank ? f[4 * j + 3] : f[43 + 4 * j];
                asm volatile("st.async.weak.shared::cluster.mbarrier::complete_tx::bytes.v4.f32 [%0], {%1,%2,%3,%4}, [%5];"
                    :: "r"(ra + j * 2048), "f"(s0), "f"(s1), "f"(s2), "f"(s3), "r"(rb) : "memory");
            }
            WG_WAIT(0);
            acc_fence<40>(e);
            mbar_wait(xb, 0);
            #pragma unroll
            for (int j = 0; j < 10; j++) {
                float s0, s1, s2, s3;
                asm volatile("ld.shared.v4.f32 {%0,%1,%2,%3}, [%4];" : "=f"(s0), "=f"(s1), "=f"(s2), "=f"(s3) : "r"(xa + j * 2048) : "memory");
                e[4 * j] += s0; e[4 * j + 1] += s1; e[4 * j + 2] += s2; e[4 * j + 3] += s3;
            }
        }
        if (tid == 128) { PROF(30); }
        mbar_wait(bars + B_QF * 8, 0);
        const int mi = lane >> 3, l8 = lane & 7;
        const uint32_t qa = sb + OFF_Q + (cw * 64 + w * 16 + (mi & 1) * 8 + l8) * 160 + (mi >> 1) * 16;
        const uint32_t za = sb + OFF_Z + cw * 10240 + ((mi >> 1) * 8 + l8) * 128 + (((2 * w + (mi & 1)) ^ l8) << 4);
        #pragma unroll
        for (int j = 0; j < 10; j += 2) {
            uint32_t qv[4], zv[4], o[4];
            if (j == 8) { mbar_wait(bars + B_ZF * 8, 0); if (tid == 128) { PROF(6); } }
            ldsm4(qa + j * 16, qv);
            ldsm4_t(za + j * 1024, zv);
            #pragma unroll
            for (int u = 0; u < 4; u++) {
                float g = (u & 1) ? g1 : g0;
                int ei = (j + (u >> 1)) * 4 + (u & 1) * 2;
                float b0 = 0.5f * e[ei], b1 = 0.5f * e[ei + 1];
                float a0 = bf_lo(qv[u]) * bf_lo(zv[u]), a1 = bf_hi(qv[u]) * bf_hi(zv[u]);
                o[u] = pack2(fmaf(g, a0 - b0, b0), fmaf(g, a1 - b1, b1));
            }
            stsm4(qa + j * 16, o[0], o[1], o[2], o[3]);
        }
        FENCE_ASYNC_S();
        __syncwarp();
        if (lane == 0) {
            tma2d_store(&tmO, sb + OFF_Q + (cw * 64 + w * 16) * 160, n2 * 80, m2 * 128 + cw * 64 + w * 16);
            asm volatile("cp.async.bulk.commit_group;" ::: "memory");
            asm volatile("cp.async.bulk.wait_group.read 0;" ::: "memory");
        }
        if (tid == 128) { PROF(7); }
    }
}

#define CHK(x) (x)
typedef CUresult (*EncodeFn)(CUtensorMap*, CUtensorMapDataType, cuuint32_t, void*, const cuuint64_t*, const cuuint64_t*, const cuuint32_t*, const cuuint32_t*,
                             CUtensorMapInterleave, CUtensorMapSwizzle, CUtensorMapL2promotion, CUtensorMapFloatOOBfill);
static void mk2d(EncodeFn enc, CUtensorMap* m, const void* p, uint64_t d0, uint64_t d1, uint32_t b0, uint32_t b1, CUtensorMapSwizzle sw) {
    cuuint64_t gd[2] = {d0, d1}; cuuint64_t gs[1] = {d0 * 2}; cuuint32_t bd[2] = {b0, b1}; cuuint32_t es[2] = {1, 1};
    CHK(enc(m, CU_TENSOR_MAP_DATA_TYPE_BFLOAT16, 2, (void*)p, gd, gs, bd, es, CU_TENSOR_MAP_INTERLEAVE_NONE, sw, CU_TENSOR_MAP_L2_PROMOTION_L2_256B, CU_TENSOR_MAP_FLOAT_OOB_FILL_NONE));
}

extern "C" void kernel_launch(void* const* d_in, const int* in_sizes, int n_in, void* d_out, int out_size) {
    static EncodeFn enc = nullptr;
    static void* p_z = nullptr;
    if (!enc) {
        void* fn = nullptr; cudaDriverEntryPointQueryResult qr;
        cudaGetDriverEntryPoint("cuTensorMapEncodeTiled", &fn, cudaEnableDefault, &qr);
        enc = (EncodeFn)fn;
        cudaGetSymbolAddress(&p_z, g_zT);
        cudaFuncSetAttribute(fused_kernel, cudaFuncAttributeMaxDynamicSharedMemorySize, SMEM_TOTAL);
    }
    CUtensorMap tX, tWg, tWu, tWg2, tWu2, tWd, tK, tQ, tZ, tO;
    for (int i = 0; i < 2; i++) {
        cuuint64_t gd[3] = {32, DM, 54}; cuuint64_t gs[2] = {DF * 2, 64}; cuuint32_t bd[3] = {32, 64, 3}; cuuint32_t es[3] = {1, 1, 1};
        CHK(enc(i ? &tWu2 : &tWg2, CU_TENSOR_MAP_DATA_TYPE_BFLOAT16, 3, d_in[7 + i], gd, gs, bd, es, CU_TENSOR_MAP_INTERLEAVE_NONE, CU_TENSOR_MAP_SWIZZLE_64B,
            CU_TENSOR_MAP_L2_PROMOTION_L2_256B, CU_TENSOR_MAP_FLOAT_OOB_FILL_NONE));
    }
    {
        cuuint64_t gd[5] = {DM, 2, 4, 4, 54}; cuuint64_t gs[4] = {1280, 10240, 2560, 40960};
        cuuint32_t bd[5] = {16, 2, 4, 4, 2}; cuuint32_t es[5] = {1, 1, 1, 1, 1};
        CHK(enc(&tWd, CU_TENSOR_MAP_DATA_TYPE_BFLOAT16, 5, d_in[9], gd, gs, bd, es, CU_TENSOR_MAP_INTERLEAVE_NONE, CU_TENSOR_MAP_SWIZZLE_32B,
            CU_TENSOR_MAP_L2_PROMOTION_L2_256B, CU_TENSOR_MAP_FLOAT_OOB_FILL_NONE));
    }
    mk2d(enc, &tK, d_in[1], DM, SEQ, 80, 131, CU_TENSOR_MAP_SWIZZLE_NONE);
    mk2d(enc, &tX, d_in[0], DM, SEQ, 64, 128, CU_TENSOR_MAP_SWIZZLE_128B);
    mk2d(enc, &tWg, d_in[7], DF, DM, 64, 64, CU_TENSOR_MAP_SWIZZLE_128B);
    mk2d(enc, &tWu, d_in[8], DF, DM, 64, 64, CU_TENSOR_MAP_SWIZZLE_128B);
    mk2d(enc, &tQ, d_in[0], DM, SEQ, 80, 128, CU_TENSOR_MAP_SWIZZLE_NONE);
    mk2d(enc, &tZ, p_z, SEQ, DM, 64, 16, CU_TENSOR_MAP_SWIZZLE_128B);
    mk2d(enc, &tO, d_out, DM, SEQ, 80, 16, CU_TENSOR_MAP_SWIZZLE_NONE);
    Params prm;
    prm.x = (const bf16*)d_in[0]; prm.k = (const bf16*)d_in[1]; prm.v = (const bf16*)d_in[2]; prm.shift_k = (const bf16*)d_in[3];
    prm.ssm_k = (const bf16*)d_in[4]; prm.ssm_D = (const bf16*)d_in[5]; prm.gate_w = (const bf16*)d_in[10]; prm.wd = (const bf16*)d_in[9]; prm.wg = (const bf16*)d_in[7]; prm.wu = (const bf16*)d_in[8];
    fused_kernel<<<128, 512, SMEM_TOTAL>>>(tX, tWg, tWu, tWg2, tWu2, tWd, tK, tQ, tZ, tO, prm);
}
```

```cpp
#include <cuda_runtime.h>
#include <cuda.h>
#include <cuda_bf16.h>
#include <stdint.h>

typedef __nv_bfloat16 bf16;
constexpr int SEQ = 2048, DM = 640, DF = 1728;

__device__ __align__(1024) bf16 g_h[SEQ * DF];
__device__ __align__(1024) bf16 g_kvT[DM * SEQ];
__device__ __align__(1024) bf16 g_zT[DM * SEQ];
__device__ __align__(1024) bf16 g_wd[DF * DM];
__device__ __align__(128) float g_gate[SEQ];
constexpr int C_KV = 0, C_KV0 = 8, C_ZL = 16, C_H1 = 24, C_H2 = 40, C_Z = 56, C_DONE = 64, C_W = 65, C_NUM = 66;
__device__ unsigned g_cnt[C_NUM * 32];
#define PROF(i)

constexpr int ST1 = 49152, NST1 = 4;
constexpr int ST2 = 36864, NST2 = 5, OFF_Q = 4 * ST2, OFF_Z = OFF_Q + 20480;
constexpr int RING = ST1 * NST1;
constexpr int CB_HB = 128, CB_HA = 4288, CB_P0 = 9280, CB_PS = 2944, CB = 14336;
constexpr int OFF_CB = RING;
constexpr int OFF_STG = OFF_CB + 2 * CB;
constexpr int OFF_KT = OFF_CB + CB, OFF_SK = OFF_CB + CB_P0 - 896;
constexpr int OFF_GW = OFF_CB + 32896, OFF_HS = 3 * ST1;
constexpr int OFF_BAR = OFF_KT + 20992;
constexpr int SMEM_TOTAL = OFF_BAR + 384;
constexpr int B_FULL1 = 0, B_EMPTY1 = 4, B_FULL2 = 8, B_EMPTY2 = 15, B_CFULL = 22, B_CDONE = 24, B_STG = 26, B_KV = 27, B_G = 28, B_CRAW = 29, B_HD = 31, B_WD = 32, B_KIN = 33, B_PRE = 34, B_QF = 13, B_ZF = 14, B_XFREE = 20, B_XF = 35, B_KV1 = 21;
#define CI 3
constexpr int NCH = 5;

#define KV_WAIT 0
#define V_WAIT -1
__device__ __forceinline__ void wgmma_ss_n128(float* d, uint64_t da, uint64_t db, int sd) {
    asm volatile("{\n.reg .pred p;\nsetp.ne.b32 p, %66, 0;\nwgmma.mma_async.sync.aligned.m64n128k16.f32.bf16.bf16 {%0,%1,%2,%3,%4,%5,%6,%7,%8,%9,%10,%11,%12,%13,%14,%15,%16,%17,%18,%19,%20,%21,%22,%23,%24,%25,%26,%27,%28,%29,%30,%31,%32,%33,%34,%35,%36,%37,%38,%39,%40,%41,%42,%43,%44,%45,%46,%47,%48,%49,%50,%51,%52,%53,%54,%55,%56,%57,%58,%59,%60,%61,%62,%63}, %64, %65, p, 1, 1, 0, 1;\n}\n"
    : "+f"(d[0]),"+f"(d[1]),"+f"(d[2]),"+f"(d[3]),"+f"(d[4]),"+f"(d[5]),"+f"(d[6]),"+f"(d[7]),"+f"(d[8]),"+f"(d[9]),"+f"(d[10]),"+f"(d[11]),"+f"(d[12]),"+f"(d[13]),"+f"(d[14]),"+f"(d[15]),"+f"(d[16]),"+f"(d[17]),"+f"(d[18]),"+f"(d[19]),"+f"(d[20]),"+f"(d[21]),"+f"(d[22]),"+f"(d[23]),"+f"(d[24]),"+f"(d[25]),"+f"(d[26]),"+f"(d[27]),"+f"(d[28]),"+f"(d[29]),"+f"(d[30]),"+f"(d[31]),"+f"(d[32]),"+f"(d[33]),"+f"(d[34]),"+f"(d[35]),"+f"(d[36]),"+f"(d[37]),"+f"(d[38]),"+f"(d[39]),"+f"(d[40]),"+f"(d[41]),"+f"(d[42]),"+f"(d[43]),"+f"(d[44]),"+f"(d[45]),"+f"(d[46]),"+f"(d[47]),"+f"(d[48]),"+f"(d[49]),"+f"(d[50]),"+f"(d[51]),"+f"(d[52]),"+f"(d[53]),"+f"(d[54]),"+f"(d[55]),"+f"(d[56]),"+f"(d[57]),"+f"(d[58]),"+f"(d[59]),"+f"(d[60]),"+f"(d[61]),"+f"(d[62]),"+f"(d[63]) : "l"(da), "l"(db), "r"(sd));
}
__device__ __forceinline__ void wgmma_ss_n192(float* d, uint64_t da, uint64_t db, int sd) {
    asm volatile("{\n.reg .pred p;\nsetp.ne.b32 p, %98, 0;\nwgmma.mma_async.sync.aligned.m64n192k16.f32.bf16.bf16 {%0,%1,%2,%3,%4,%5,%6,%7,%8,%9,%10,%11,%12,%13,%14,%15,%16,%17,%18,%19,%20,%21,%22,%23,%24,%25,%26,%27,%28,%29,%30,%31,%32,%33,%34,%35,%36,%37,%38,%39,%40,%41,%42,%43,%44,%45,%46,%47,%48,%49,%50,%51,%52,%53,%54,%55,%56,%57,%58,%59,%60,%61,%62,%63,%64,%65,%66,%67,%68,%69,%70,%71,%72,%73,%74,%75,%76,%77,%78,%79,%80,%81,%82,%83,%84,%85,%86,%87,%88,%89,%90,%91,%92,%93,%94,%95}, %96, %97, p, 1, 1, 0, 1;\n}\n"
    : "+f"(d[0]),"+f"(d[1]),"+f"(d[2]),"+f"(d[3]),"+f"(d[4]),"+f"(d[5]),"+f"(d[6]),"+f"(d[7]),"+f"(d[8]),"+f"(d[9]),"+f"(d[10]),"+f"(d[11]),"+f"(d[12]),"+f"(d[13]),"+f"(d[14]),"+f"(d[15]),"+f"(d[16]),"+f"(d[17]),"+f"(d[18]),"+f"(d[19]),"+f"(d[20]),"+f"(d[21]),"+f"(d[22]),"+f"(d[23]),"+f"(d[24]),"+f"(d[25]),"+f"(d[26]),"+f"(d[27]),"+f"(d[28]),"+f"(d[29]),"+f"(d[30]),"+f"(d[31]),"+f"(d[32]),"+f"(d[33]),"+f"(d[34]),"+f"(d[35]),"+f"(d[36]),"+f"(d[37]),"+f"(d[38]),"+f"(d[39]),"+f"(d[40]),"+f"(d[41]),"+f"(d[42]),"+f"(d[43]),"+f"(d[44]),"+f"(d[45]),"+f"(d[46]),"+f"(d[47]),"+f"(d[48]),"+f"(d[49]),"+f"(d[50]),"+f"(d[51]),"+f"(d[52]),"+f"(d[53]),"+f"(d[54]),"+f"(d[55]),"+f"(d[56]),"+f"(d[57]),"+f"(d[58]),"+f"(d[59]),"+f"(d[60]),"+f"(d[61]),"+f"(d[62]),"+f"(d[63]),"+f"(d[64]),"+f"(d[65]),"+f"(d[66]),"+f"(d[67]),"+f"(d[68]),"+f"(d[69]),"+f"(d[70]),"+f"(d[71]),"+f"(d[72]),"+f"(d[73]),"+f"(d[74]),"+f"(d[75]),"+f"(d[76]),"+f"(d[77]),"+f"(d[78]),"+f"(d[79]),"+f"(d[80]),"+f"(d[81]),"+f"(d[82]),"+f"(d[83]),"+f"(d[84]),"+f"(d[85]),"+f"(d[86]),"+f"(d[87]),"+f"(d[88]),"+f"(d[89]),"+f"(d[90]),"+f"(d[91]),"+f"(d[92]),"+f"(d[93]),"+f"(d[94]),"+f"(d[95]) : "l"(da), "l"(db), "r"(sd));
}
__device__ __forceinline__ void wgmma_ss_n160(float* d, uint64_t da, uint64_t db, int sd) {
    asm volatile("{\n.reg .pred p;\nsetp.ne.b32 p, %82, 0;\nwgmma.mma_async.sync.aligned.m64n160k16.f32.bf16.bf16 {%0,%1,%2,%3,%4,%5,%6,%7,%8,%9,%10,%11,%12,%13,%14,%15,%16,%17,%18,%19,%20,%21,%22,%23,%24,%25,%26,%27,%28,%29,%30,%31,%32,%33,%34,%35,%36,%37,%38,%39,%40,%41,%42,%43,%44,%45,%46,%47,%48,%49,%50,%51,%52,%53,%54,%55,%56,%57,%58,%59,%60,%61,%62,%63,%64,%65,%66,%67,%68,%69,%70,%71,%72,%73,%74,%75,%76,%77,%78,%79}, %80, %81, p, 1, 1, 0, 1;\n}\n"
    : "+f"(d[0]),"+f"(d[1]),"+f"(d[2]),"+f"(d[3]),"+f"(d[4]),"+f"(d[5]),"+f"(d[6]),"+f"(d[7]),"+f"(d[8]),"+f"(d[9]),"+f"(d[10]),"+f"(d[11]),"+f"(d[12]),"+f"(d[13]),"+f"(d[14]),"+f"(d[15]),"+f"(d[16]),"+f"(d[17]),"+f"(d[18]),"+f"(d[19]),"+f"(d[20]),"+f"(d[21]),"+f"(d[22]),"+f"(d[23]),"+f"(d[24]),"+f"(d[25]),"+f"(d[26]),"+f"(d[27]),"+f"(d[28]),"+f"(d[29]),"+f"(d[30]),"+f"(d[31]),"+f"(d[32]),"+f"(d[33]),"+f"(d[34]),"+f"(d[35]),"+f"(d[36]),"+f"(d[37]),"+f"(d[38]),"+f"(d[39]),"+f"(d[40]),"+f"(d[41]),"+f"(d[42]),"+f"(d[43]),"+f"(d[44]),"+f"(d[45]),"+f"(d[46]),"+f"(d[47]),"+f"(d[48]),"+f"(d[49]),"+f"(d[50]),"+f"(d[51]),"+f"(d[52]),"+f"(d[53]),"+f"(d[54]),"+f"(d[55]),"+f"(d[56]),"+f"(d[57]),"+f"(d[58]),"+f"(d[59]),"+f"(d[60]),"+f"(d[61]),"+f"(d[62]),"+f"(d[63]),"+f"(d[64]),"+f"(d[65]),"+f"(d[66]),"+f"(d[67]),"+f"(d[68]),"+f"(d[69]),"+f"(d[70]),"+f"(d[71]),"+f"(d[72]),"+f"(d[73]),"+f"(d[74]),"+f"(d[75]),"+f"(d[76]),"+f"(d[77]),"+f"(d[78]),"+f"(d[79]) : "l"(da), "l"(db), "r"(sd));
}
__device__ __forceinline__ void wgmma_ss_n80(float* d, uint64_t da, uint64_t db, int sd) {
    asm volatile("{\n.reg .pred p;\nsetp.ne.b32 p, %42, 0;\nwgmma.mma_async.sync.aligned.m64n80k16.f32.bf16.bf16 {%0,%1,%2,%3,%4,%5,%6,%7,%8,%9,%10,%11,%12,%13,%14,%15,%16,%17,%18,%19,%20,%21,%22,%23,%24,%25,%26,%27,%28,%29,%30,%31,%32,%33,%34,%35,%36,%37,%38,%39}, %40, %41, p, 1, 1, 0, 1;\n}\n"
    : "+f"(d[0]),"+f"(d[1]),"+f"(d[2]),"+f"(d[3]),"+f"(d[4]),"+f"(d[5]),"+f"(d[6]),"+f"(d[7]),"+f"(d[8]),"+f"(d[9]),"+f"(d[10]),"+f"(d[11]),"+f"(d[12]),"+f"(d[13]),"+f"(d[14]),"+f"(d[15]),"+f"(d[16]),"+f"(d[17]),"+f"(d[18]),"+f"(d[19]),"+f"(d[20]),"+f"(d[21]),"+f"(d[22]),"+f"(d[23]),"+f"(d[24]),"+f"(d[25]),"+f"(d[26]),"+f"(d[27]),"+f"(d[28]),"+f"(d[29]),"+f"(d[30]),"+f"(d[31]),"+f"(d[32]),"+f"(d[33]),"+f"(d[34]),"+f"(d[35]),"+f"(d[36]),"+f"(d[37]),"+f"(d[38]),"+f"(d[39]) : "l"(da), "l"(db), "r"(sd));
}
template<int SD> __device__ __forceinline__ void wgmma_rs_n16(float* d, const uint32_t* a, uint64_t db) {
    asm volatile("wgmma.mma_async.sync.aligned.m64n16k16.f32.bf16.bf16 {%0,%1,%2,%3,%4,%5,%6,%7}, {%8,%9,%10,%11}, %12, %13, 1, 1, 0;\n"
    : "+f"(d[0]),"+f"(d[1]),"+f"(d[2]),"+f"(d[3]),"+f"(d[4]),"+f"(d[5]),"+f"(d[6]),"+f"(d[7]) : "r"(a[0]), "r"(a[1]), "r"(a[2]), "r"(a[3]), "l"(db), "n"(SD));
}
template<int SD> __device__ __forceinline__ void wgmma_rs_n32(float* d, const uint32_t* a, uint64_t db) {
    asm volatile("wgmma.mma_async.sync.aligned.m64n32k16.f32.bf16.bf16 {%0,%1,%2,%3,%4,%5,%6,%7,%8,%9,%10,%11,%12,%13,%14,%15}, {%16,%17,%18,%19}, %20, %21, 1, 1, 0;\n"
    : "+f"(d[0]),"+f"(d[1]),"+f"(d[2]),"+f"(d[3]),"+f"(d[4]),"+f"(d[5]),"+f"(d[6]),"+f"(d[7]),"+f"(d[8]),"+f"(d[9]),"+f"(d[10]),"+f"(d[11]),"+f"(d[12]),"+f"(d[13]),"+f"(d[14]),"+f"(d[15]) : "r"(a[0]), "r"(a[1]), "r"(a[2]), "r"(a[3]), "l"(db), "n"(SD));
}
template<int SD> __device__ __forceinline__ void wgmma_rs_n48(float* d, const uint32_t* a, uint64_t db) {
    asm volatile("wgmma.mma_async.sync.aligned.m64n48k16.f32.bf16.bf16 {%0,%1,%2,%3,%4,%5,%6,%7,%8,%9,%10,%11,%12,%13,%14,%15,%16,%17,%18,%19,%20,%21,%22,%23}, {%24,%25,%26,%27}, %28, %29, 1, 1, 0;\n"
    : "+f"(d[0]),"+f"(d[1]),"+f"(d[2]),"+f"(d[3]),"+f"(d[4]),"+f"(d[5]),"+f"(d[6]),"+f"(d[7]),"+f"(d[8]),"+f"(d[9]),"+f"(d[10]),"+f"(d[11]),"+f"(d[12]),"+f"(d[13]),"+f"(d[14]),"+f"(d[15]),"+f"(d[16]),"+f"(d[17]),"+f"(d[18]),"+f"(d[19]),"+f"(d[20]),"+f"(d[21]),"+f"(d[22]),"+f"(d[23]) : "r"(a[0]), "r"(a[1]), "r"(a[2]), "r"(a[3]), "l"(db), "n"(SD));
}
template<int SD> __device__ __forceinline__ void wgmma_rs_n64(float* d, const uint32_t* a, uint64_t db) {
    asm volatile("wgmma.mma_async.sync.aligned.m64n64k16.f32.bf16.bf16 {%0,%1,%2,%3,%4,%5,%6,%7,%8,%9,%10,%11,%12,%13,%14,%15,%16,%17,%18,%19,%20,%21,%22,%23,%24,%25,%26,%27,%28,%29,%30,%31}, {%32,%33,%34,%35}, %36, %37, 1, 1, 0;\n"
    : "+f"(d[0]),"+f"(d[1]),"+f"(d[2]),"+f"(d[3]),"+f"(d[4]),"+f"(d[5]),"+f"(d[6]),"+f"(d[7]),"+f"(d[8]),"+f"(d[9]),"+f"(d[10]),"+f"(d[11]),"+f"(d[12]),"+f"(d[13]),"+f"(d[14]),"+f"(d[15]),"+f"(d[16]),"+f"(d[17]),"+f"(d[18]),"+f"(d[19]),"+f"(d[20]),"+f"(d[21]),"+f"(d[22]),"+f"(d[23]),"+f"(d[24]),"+f"(d[25]),"+f"(d[26]),"+f"(d[27]),"+f"(d[28]),"+f"(d[29]),"+f"(d[30]),"+f"(d[31]) : "r"(a[0]), "r"(a[1]), "r"(a[2]), "r"(a[3]), "l"(db), "n"(SD));
}
template<int SD> __device__ __forceinline__ void wgmma_rs_n96(float* d, const uint32_t* a, uint64_t db) {
    asm volatile("wgmma.mma_async.sync.aligned.m64n96k16.f32.bf16.bf16 {%0,%1,%2,%3,%4,%5,%6,%7,%8,%9,%10,%11,%12,%13,%14,%15,%16,%17,%18,%19,%20,%21,%22,%23,%24,%25,%26,%27,%28,%29,%30,%31,%32,%33,%34,%35,%36,%37,%38,%39,%40,%41,%42,%43,%44,%45,%46,%47}, {%48,%49,%50,%51}, %52, %53, 1, 1, 0;\n"
    : "+f"(d[0]),"+f"(d[1]),"+f"(d[2]),"+f"(d[3]),"+f"(d[4]),"+f"(d[5]),"+f"(d[6]),"+f"(d[7]),"+f"(d[8]),"+f"(d[9]),"+f"(d[10]),"+f"(d[11]),"+f"(d[12]),"+f"(d[13]),"+f"(d[14]),"+f"(d[15]),"+f"(d[16]),"+f"(d[17]),"+f"(d[18]),"+f"(d[19]),"+f"(d[20]),"+f"(d[21]),"+f"(d[22]),"+f"(d[23]),"+f"(d[24]),"+f"(d[25]),"+f"(d[26]),"+f"(d[27]),"+f"(d[28]),"+f"(d[29]),"+f"(d[30]),"+f"(d[31]),"+f"(d[32]),"+f"(d[33]),"+f"(d[34]),"+f"(d[35]),"+f"(d[36]),"+f"(d[37]),"+f"(d[38]),"+f"(d[39]),"+f"(d[40]),"+f"(d[41]),"+f"(d[42]),"+f"(d[43]),"+f"(d[44]),"+f"(d[45]),"+f"(d[46]),"+f"(d[47]) : "r"(a[0]), "r"(a[1]), "r"(a[2]), "r"(a[3]), "l"(db), "n"(SD));
}
template<int SD> __device__ __forceinline__ void wgmma_rs_n128(float* d, const uint32_t* a, uint64_t db) {
    asm volatile("wgmma.mma_async.sync.aligned.m64n128k16.f32.bf16.bf16 {%0,%1,%2,%3,%4,%5,%6,%7,%8,%9,%10,%11,%12,%13,%14,%15,%16,%17,%18,%19,%20,%21,%22,%23,%24,%25,%26,%27,%28,%29,%30,%31,%32,%33,%34,%35,%36,%37,%38,%39,%40,%41,%42,%43,%44,%45,%46,%47,%48,%49,%50,%51,%52,%53,%54,%55,%56,%57,%58,%59,%60,%61,%62,%63}, {%64,%65,%66,%67}, %68, %69, 1, 1, 0;\n"
    : "+f"(d[0]),"+f"(d[1]),"+f"(d[2]),"+f"(d[3]),"+f"(d[4]),"+f"(d[5]),"+f"(d[6]),"+f"(d[7]),"+f"(d[8]),"+f"(d[9]),"+f"(d[10]),"+f"(d[11]),"+f"(d[12]),"+f"(d[13]),"+f"(d[14]),"+f"(d[15]),"+f"(d[16]),"+f"(d[17]),"+f"(d[18]),"+f"(d[19]),"+f"(d[20]),"+f"(d[21]),"+f"(d[22]),"+f"(d[23]),"+f"(d[24]),"+f"(d[25]),"+f"(d[26]),"+f"(d[27]),"+f"(d[28]),"+f"(d[29]),"+f"(d[30]),"+f"(d[31]),"+f"(d[32]),"+f"(d[33]),"+f"(d[34]),"+f"(d[35]),"+f"(d[36]),"+f"(d[37]),"+f"(d[38]),"+f"(d[39]),"+f"(d[40]),"+f"(d[41]),"+f"(d[42]),"+f"(d[43]),"+f"(d[44]),"+f"(d[45]),"+f"(d[46]),"+f"(d[47]),"+f"(d[48]),"+f"(d[49]),"+f"(d[50]),"+f"(d[51]),"+f"(d[52]),"+f"(d[53]),"+f"(d[54]),"+f"(d[55]),"+f"(d[56]),"+f"(d[57]),"+f"(d[58]),"+f"(d[59]),"+f"(d[60]),"+f"(d[61]),"+f"(d[62]),"+f"(d[63]) : "r"(a[0]), "r"(a[1]), "r"(a[2]), "r"(a[3]), "l"(db), "n"(SD));
}
template<int N, int SD> __device__ __forceinline__ void wgmma_rs(float* d, const uint32_t* a, uint64_t db) {
    if constexpr (N == 16) wgmma_rs_n16<SD>(d, a, db);
    if constexpr (N == 32) wgmma_rs_n32<SD>(d, a, db);
    if constexpr (N == 48) wgmma_rs_n48<SD>(d, a, db);
    if constexpr (N == 64) wgmma_rs_n64<SD>(d, a, db);
    if constexpr (N == 96) wgmma_rs_n96<SD>(d, a, db);
    if constexpr (N == 128) wgmma_rs_n128<SD>(d, a, db);
}

__device__ __forceinline__ uint64_t make_desc(uint32_t saddr, uint32_t lbo, uint32_t sbo, uint32_t swz) {
    uint64_t d = 0;
    d |= (uint64_t)((saddr & 0x3FFFF) >> 4);
    d |= (uint64_t)((lbo & 0x3FFFF) >> 4) << 16;
    d |= (uint64_t)((sbo & 0x3FFFF) >> 4) << 32;
    d |= (uint64_t)swz << 62;
    return d;
}
#define WG_FENCE() asm volatile("wgmma.fence.sync.aligned;\n" ::: "memory")
#define WG_COMMIT() asm volatile("wgmma.commit_group.sync.aligned;\n" ::: "memory")
#define WG_WAIT(n) asm volatile("wgmma.wait_group.sync.aligned %0;\n" :: "n"(n) : "memory")
#define PP_SYNC() asm volatile("bar.sync %0, 256;" :: "r"(2 + cw) : "memory")
#define PP_ARRIVE() asm volatile("bar.arrive %0, 256;" :: "r"(3 - cw) : "memory")
#define FENCE_ASYNC_S() asm volatile("fence.proxy.async.shared::cta;\n" ::: "memory")
#define FENCE_ASYNC_G() asm volatile("fence.proxy.async.global;\n" ::: "memory")

__device__ __forceinline__ void mbar_init(uint32_t bar, uint32_t cnt) { asm volatile("mbarrier.init.shared::cta.b64 [%0], %1;" :: "r"(bar), "r"(cnt)); }
__device__ __forceinline__ void mbar_expect_tx(uint32_t bar, uint32_t bytes) { asm volatile("mbarrier.arrive.expect_tx.shared::cta.b64 _, [%0], %1;" :: "r"(bar), "r"(bytes) : "memory"); }
__device__ __forceinline__ void mbar_arrive(uint32_t bar) { asm volatile("mbarrier.arrive.shared::cta.b64 _, [%0];" :: "r"(bar) : "memory"); }
__device__ __forceinline__ bool mbar_try(uint32_t bar, uint32_t parity) {
    uint32_t ok;
    asm volatile("{\n.reg .pred p;\nmbarrier.try_wait.parity.shared::cta.b64 p, [%1], %2;\nselp.u32 %0, 1, 0, p;\n}\n" : "=r"(ok) : "r"(bar), "r"(parity) : "memory");
    return ok != 0;
}
__device__ __forceinline__ void mbar_wait(uint32_t bar, uint32_t parity) {
    if (mbar_try(bar, parity)) return;
    if (mbar_try(bar, parity)) return;
    long long t0 = clock64();
    while (!mbar_try(bar, parity)) { if (clock64() - t0 > 100000000LL) break; }
}
__device__ __forceinline__ void mbar_arrive_cluster(uint32_t bar, uint32_t cta) {
    asm volatile("{\n.reg .b32 ra;\nmapa.shared::cluster.u32 ra, %0, %1;\nmbarrier.arrive.shared::cluster.b64 _, [ra];\n}\n" :: "r"(bar), "r"(cta) : "memory");
}
__device__ __forceinline__ void tma2d(uint32_t dst, const CUtensorMap* tm, int c0, int c1, uint32_t bar) {
    asm volatile("cp.async.bulk.tensor.2d.shared::cluster.global.mbarrier::complete_tx::bytes [%0], [%1, {%3, %4}], [%2];"
        :: "r"(dst), "l"(tm), "r"(bar), "r"(c0), "r"(c1) : "memory");
}
__device__ __forceinline__ void tma2d_mc(uint32_t dst, const CUtensorMap* tm, int c0, int c1, uint32_t bar) {
    asm volatile("cp.async.bulk.tensor.2d.shared::cluster.global.mbarrier::complete_tx::bytes.multicast::cluster [%0], [%1, {%3, %4}], [%2], %5;"
        :: "r"(dst), "l"(tm), "r"(bar), "r"(c0), "r"(c1), "h"((uint16_t)3) : "memory");
}
__device__ __forceinline__ void bulk_load(uint32_t dst, const void* src, uint32_t bytes, uint32_t bar) {
    asm volatile("cp.async.bulk.shared::cluster.global.mbarrier::complete_tx::bytes [%0], [%1], %2, [%3];"
        :: "r"(dst), "l"(src), "r"(bytes), "r"(bar) : "memory");
}
__device__ __forceinline__ void tma3d_mc(uint32_t dst, const CUtensorMap* tm, int c1, int c2, uint32_t bar) {
    asm volatile("cp.async.bulk.tensor.3d.shared::cluster.global.mbarrier::complete_tx::bytes.multicast::cluster [%0], [%1, {%3, %4, %5}], [%2], %6;"
        :: "r"(dst), "l"(tm), "r"(bar), "r"(0), "r"(c1), "r"(c2), "h"((uint16_t)3) : "memory");
}
__device__ __forceinline__ void tma5d(uint32_t dst, const CUtensorMap* tm, int c0, int c4, uint32_t bar) {
    asm volatile("cp.async.bulk.tensor.5d.shared::cluster.global.mbarrier::complete_tx::bytes [%0], [%1, {%4, %3, %3, %3, %5}], [%2];"
        :: "r"(dst), "l"(tm), "r"(bar), "r"(0), "r"(c0), "r"(c4) : "memory");
}
__device__ __forceinline__ void l2_prefetch(const void* src, uint32_t bytes) {
    asm volatile("cp.async.bulk.prefetch.L2.global [%0], %1;" :: "l"(src), "r"(bytes) : "memory");
}
__device__ __forceinline__ void bulk_store(void* dst, uint32_t src, uint32_t bytes) {
    asm volatile("cp.async.bulk.global.shared::cta.bulk_group [%0], [%1], %2;" :: "l"(dst), "r"(src), "r"(bytes) : "memory");
}
__device__ __forceinline__ void tma2d_store(const CUtensorMap* tm, uint32_t src, int c0, int c1) {
    asm volatile("cp.async.bulk.tensor.2d.global.shared::cta.bulk_group [%0, {%2, %3}], [%1];" :: "l"(tm), "r"(src), "r"(c0), "r"(c1) : "memory");
}
__device__ __forceinline__ void cluster_sync_all() {
    asm volatile("barrier.cluster.arrive.relaxed;\nbarrier.cluster.wait;\n" ::: "memory");
}
__device__ __forceinline__ void wait_cnt(int idx, unsigned target) {
    const unsigned* p = &g_cnt[idx * 32];
    unsigned v;
    asm volatile("ld.relaxed.gpu.global.u32 %0, [%1];" : "=r"(v) : "l"(p) : "memory");
    if (v >= target) return;
    long long t0 = clock64();
    do {
        __nanosleep(40);
        asm volatile("ld.relaxed.gpu.global.u32 %0, [%1];" : "=r"(v) : "l"(p) : "memory");
        if (clock64() - t0 > 100000000LL) break;
    } while (v < target);
}
__device__ __forceinline__ void signal_cnt(int idx) {
    asm volatile("red.release.gpu.global.add.u32 [%0], 1;" :: "l"(&g_cnt[idx * 32]) : "memory");
}
__device__ __forceinline__ void signal_cnt_bulk(int idx) {
    asm volatile("red.relaxed.gpu.global.add.u32 [%0], 1;" :: "l"(&g_cnt[idx * 32]) : "memory");
}
__device__ __forceinline__ uint32_t pack2(float lo, float hi) {
    uint32_t r; asm("cvt.rn.bf16x2.f32 %0, %1, %2;" : "=r"(r) : "f"(hi), "f"(lo)); return r;
}
__device__ __forceinline__ uint32_t hmul2(uint32_t a, uint32_t b) { uint32_t r; asm("mul.rn.bf16x2 %0, %1, %2;" : "=r"(r) : "r"(a), "r"(b)); return r; }
__device__ __forceinline__ uint32_t hfma2(uint32_t a, uint32_t b, uint32_t c) { uint32_t r; asm("fma.rn.bf16x2 %0, %1, %2, %3;" : "=r"(r) : "r"(a), "r"(b), "r"(c)); return r; }
__device__ __forceinline__ float bf_lo(uint32_t v) { return __uint_as_float(v << 16); }
__device__ __forceinline__ float bf_hi(uint32_t v) { return __uint_as_float(v & 0xFFFF0000u); }
__device__ __forceinline__ float geglu(float g, float u) {
    float in = g * fmaf(g * g, 0.0356774081f, 0.7978845608f);
    float t; asm("tanh.approx.f32 %0, %1;" : "=f"(t) : "f"(in));
    float gu = g * u;
    return fmaf(gu, t, gu);
}
__device__ __forceinline__ uint32_t lds32(uint32_t a) { uint32_t v; asm volatile("ld.shared.u32 %0, [%1];" : "=r"(v) : "r"(a)); return v; }
__device__ __forceinline__ float lds_bf(uint32_t a) { uint16_t v; asm volatile("ld.shared.u16 %0, [%1];" : "=h"(v) : "r"(a)); return __uint_as_float((uint32_t)v << 16); }
__device__ __forceinline__ float2 lds64f(uint32_t a) { float2 v; asm volatile("ld.shared.v2.f32 {%0,%1}, [%2];" : "=f"(v.x), "=f"(v.y) : "r"(a)); return v; }
__device__ __forceinline__ void sts64f(uint32_t a, float x, float y) { asm volatile("st.shared.v2.f32 [%0], {%1,%2};" :: "r"(a), "f"(x), "f"(y) : "memory"); }
__device__ __forceinline__ void stsm4_t(uint32_t a, uint32_t r0, uint32_t r1, uint32_t r2, uint32_t r3) {
    asm volatile("stmatrix.sync.aligned.m8n8.x4.trans.shared.b16 [%0], {%1,%2,%3,%4};" :: "r"(a), "r"(r0), "r"(r1), "r"(r2), "r"(r3) : "memory");
}
__device__ __forceinline__ void stsm4(uint32_t a, uint32_t r0, uint32_t r1, uint32_t r2, uint32_t r3) {
    asm volatile("stmatrix.sync.aligned.m8n8.x4.shared.b16 [%0], {%1,%2,%3,%4};" :: "r"(a), "r"(r0), "r"(r1), "r"(r2), "r"(r3) : "memory");
}
__device__ __forceinline__ void ldsm4(uint32_t a, uint32_t* r) {
    asm volatile("ldmatrix.sync.aligned.m8n8.x4.shared.b16 {%0,%1,%2,%3}, [%4];" : "=r"(r[0]), "=r"(r[1]), "=r"(r[2]), "=r"(r[3]) : "r"(a) : "memory");
}
__device__ __forceinline__ void ldsm4_t(uint32_t a, uint32_t* r) {
    asm volatile("ldmatrix.sync.aligned.m8n8.x4.trans.shared.b16 {%0,%1,%2,%3}, [%4];" : "=r"(r[0]), "=r"(r[1]), "=r"(r[2]), "=r"(r[3]) : "r"(a) : "memory");
}

__device__ __forceinline__ void zero_pad(uint32_t cb, int j) {
    int off = j < 8 ? j * 16 : (j < 12 ? 4224 + (j - 8) * 16 : (j < 68 ? CB_P0 - 896 + (j - 12) * 16 : CB_P0 + CB_PS - 896 + (j - 68) * 16));
    asm volatile("st.shared.v4.u32 [%0], {%1,%1,%1,%1};" :: "r"(cb + off), "r"(0) : "memory");
}

struct Params {
    const bf16 *x, *k, *v, *shift_k, *ssm_k, *ssm_D, *gate_w, *wd, *wg, *wu;
};

template<int N, int SD> __device__ __forceinline__ void conv_group(float* acc, const uint32_t* a, uint64_t db0) {
    WG_FENCE();
    wgmma_rs<N, SD>(acc, a + 0, db0);
    wgmma_rs<N, 1>(acc, a + 4, db0 - 1);
    wgmma_rs<N, 1>(acc, a + 8, db0 - 4);
    wgmma_rs<N, 1>(acc, a + 12, db0 - 5);
    WG_COMMIT();
}
template<int NO> __device__ __forceinline__ void acc_widen(float* n, float* o) {
    #pragma unroll
    for (int j = 0; j < 8; j++) asm volatile("mov.b32 %0, 0;" : "=f"(n[j]) :: "memory");
    #pragma unroll
    for (int j = 0; j < NO; j++) asm volatile("add.f32 %0, %1, 0f00000000;" : "=f"(n[8 + j]) : "f"(o[j]) : "memory");
}
template<int N> __device__ __forceinline__ void acc_fence(float* o) {
    #pragma unroll
    for (int j = 0; j < N; j++) asm volatile("" : "+f"(o[j]) :: "memory");
}
__device__ __forceinline__ void conv_loadA(uint32_t* a, uint32_t addr) {
    #pragma unroll
    for (int s = 0; s < 4; s++) {
        uint32_t o = addr + ((s & 1) + (s >> 1) * 4) * 32;
        a[4 * s + 0] = lds32(o);
        a[4 * s + 1] = lds32(o + 256);
        a[4 * s + 2] = lds32(o + 16);
        a[4 * s + 3] = lds32(o + 272);
    }
}
#define AFENCE(a) _Pragma("unroll") for (int _i = 0; _i < 16; _i++) asm volatile("" : "+r"(a[_i]) :: "memory")

__global__ void __cluster_dims__(2, 1, 1) __launch_bounds__(512, 1)
fused_kernel(const __grid_constant__ CUtensorMap tmX, const __grid_constant__ CUtensorMap tmWg, const __grid_constant__ CUtensorMap tmWu,
             const __grid_constant__ CUtensorMap tmWg2, const __grid_constant__ CUtensorMap tmWu2, const __grid_constant__ CUtensorMap tmWd,
             const __grid_constant__ CUtensorMap tmK, const __grid_constant__ CUtensorMap tmQ,
             const __grid_constant__ CUtensorMap tmZ, const __grid_constant__ CUtensorMap tmO,
             const Params prm) {
    extern __shared__ __align__(1024) uint8_t smem_raw[];
    const uint32_t sb = (uint32_t)__cvta_generic_to_shared(smem_raw);
    const uint32_t bars = sb + OFF_BAR;
    const int tid = threadIdx.x, wg = tid >> 7, warp = tid >> 5, lane = tid & 31;
    const int bid = blockIdx.x, rank = bid & 1, cl = bid >> 1;
    const int m1 = 2 * (cl & 7) + rank, role = cl >> 3;
#define ROT 0
    const int rot = ROT == 0 ? 0 : (ROT == 1 ? (role + (cl & 7)) % 10 : (ROT == 2 ? 5 * ((role + cl) & 1) : (3 * ((role + cl) & 3)) % 10));
    const int m2 = cl & 15, n2 = 2 * (cl >> 4) + rank;
    if (tid == 0) {
        for (int i = 0; i < NST1; i++) { mbar_init(bars + (B_FULL1 + i) * 8, 1); mbar_init(bars + (B_EMPTY1 + i) * 8, 4); }
        for (int i = 0; i < NST2; i++) { mbar_init(bars + (B_FULL2 + i) * 8, 1); mbar_init(bars + (B_EMPTY2 + i) * 8, 2); }
        mbar_init(bars + B_QF * 8, 1); mbar_init(bars + B_ZF * 8, 1); mbar_init(bars + B_XFREE * 8, 2);
        for (int i = 0; i < 2; i++) { mbar_init(bars + (B_XF + i) * 8, 1); mbar_expect_tx(bars + (B_XF + i) * 8, 20480); }
        for (int i = 0; i < 2; i++) { mbar_init(bars + (B_CFULL + i) * 8, 2); mbar_init(bars + (B_CDONE + i) * 8, 4); mbar_init(bars + (B_CRAW + i) * 8, 1); }
        mbar_init(bars + B_HD * 8, 8); mbar_init(bars + B_WD * 8, 1); mbar_init(bars + B_KIN * 8, 1); mbar_init(bars + B_PRE * 8, 4); mbar_init(bars + B_STG * 8, 1); mbar_init(bars + B_KV * 8, 4); mbar_init(bars + B_KV1 * 8, 4); mbar_init(bars + B_G * 8, 1);
        asm volatile("fence.mbarrier_init.release.cluster;" ::: "memory");
    }
    if (tid >= 384 && tid < 396) zero_pad(sb + OFF_CB, tid - 384);
    __syncthreads();
    cluster_sync_all();

    if (wg == 0) {
        asm volatile("setmaxnreg.dec.sync.aligned.u32 24;\n");
        if (warp == 0 && lane == 0) {
            const CUtensorMap* tw = rank == 0 ? &tmWg : &tmWu;
            PROF(29);
            for (int it = 0; it < 20; it++) {
                int st = it & 3;
                mbar_wait(bars + (B_EMPTY1 + st) * 8, ((it >> 2) & 1) ^ 1);
                uint32_t full = bars + (B_FULL1 + st) * 8;
                uint32_t sa = sb + st * ST1;
                if (it < 10) {
                    mbar_expect_tx(full, ST1);
                    int kb = it + rot; if (kb >= 10) kb -= 10;
                    tma2d_mc(sa + 16384 + rank * 16384, tw, role * 128, kb * 64, full);
                    tma2d_mc(sa + 24576 + rank * 16384, tw, role * 128 + 64, kb * 64, full);
                    tma2d(sa, &tmX, kb * 64, m1 * 128, full);
                } else {
                    int kb = (it < 14 ? it - 4 : it - 14) + rot; if (kb >= 10) kb -= 10;
                    mbar_expect_tx(full, it < 14 ? 24576 : 40960);
                    tma3d_mc(sa + 16384 + rank * 12288, rank == 0 ? &tmWg2 : &tmWu2, kb * 64, 32 + 3 * role, full);
                    if (it >= 14) tma2d(sa, &tmX, kb * 64, m1 * 128, full);
                    if (it < 13 && bid < 120) {
                        if (it == 10) mbar_expect_tx(bars + B_WD * 8, 9 * 2048);
                        for (int q = 0; q < 3; q++) {
                            int pi = bid * 9 + (it - 10) * 3 + q, img = pi / 10, np = img / 27;
                            tma5d(sa + 40960 + q * 2048, &tmWd, np * 160 + (pi - img * 10) * 16, (img - np * 27) * 2, bars + B_WD * 8);
                        }
                    }
                }
            }
            wait_cnt(C_W, 120);
            wait_cnt(C_H1 + m2, 8);
            FENCE_ASYNC_G();
            PROF(8);
            int st = 0; uint32_t ph = 1;
            for (int it = 0; it < 14; it++) {
                if (it != 4) {
                    if (it < 5) mbar_wait(bars + (B_EMPTY1 + (it < 3 ? it : it - 1)) * 8, 0);
                    else mbar_wait(bars + (B_EMPTY2 + st) * 8, ph);
                    uint32_t full = bars + (B_FULL2 + st) * 8;
                    uint32_t sa = sb + st * ST2;
                    int kb = it < 13 ? 2 * it + rank : 26;
                    mbar_expect_tx(full, it < 13 ? ST2 : 26624);
                    bulk_load(sa + 16384, g_wd + ((cl >> 4) * 27 + kb) * 10240 + (it < 13 ? 0 : rank * 5120), it < 13 ? 20480 : 10240, full);
                    if (it < 8) bulk_load(sa, g_h + (m2 * 27 + kb) * 8192, 16384, full);
                }
                if (++st == NST2) { st = 0; ph ^= 1; }
            }
            mbar_wait(bars + (B_EMPTY2 + 4) * 8, 1);
            mbar_expect_tx(bars + B_QF * 8, 20480 + 16384);
            tma2d(sb + OFF_Q, &tmQ, n2 * 80, m2 * 128, bars + B_QF * 8);
            PROF(10);
            wait_cnt(C_Z + n2, 64);
            FENCE_ASYNC_G();
            for (int i = 0; i < 8; i++) tma2d(sb + OFF_Z + (i & 1) * 10240 + (i >> 1) * 2048, &tmZ, m2 * 128 + (i & 1) * 64, n2 * 80 + (i >> 1) * 16, bars + B_QF * 8);
            wait_cnt(C_ZL + n2, 16);
            FENCE_ASYNC_G();
            PROF(11);
            mbar_expect_tx(bars + B_ZF * 8, 4096);
            tma2d(sb + OFF_Z + 8192, &tmZ, m2 * 128, n2 * 80 + 64, bars + B_ZF * 8);
            tma2d(sb + OFF_Z + 10240 + 8192, &tmZ, m2 * 128 + 64, n2 * 80 + 64, bars + B_ZF * 8);
            if (atomicAdd(&g_cnt[C_DONE * 32], 1u) == 127u) {
                for (int i = 0; i < C_NUM; i++) g_cnt[i * 32] = 0;
            }
        } else if (warp == 1 && lane == 0) {
            const int ch0 = (bid >> 4) * 80 + (bid & 15);
            auto load_h = [&](int i) {
                uint32_t cb = sb + OFF_CB + (i & 1) * CB, full = bars + (B_CRAW + (i & 1)) * 8;
                mbar_expect_tx(full, 4096);
                bulk_load(cb + CB_HA, prm.ssm_k + (ch0 + 16 * i) * SEQ, 4096, full);
            };
            auto load_x = [&](int i) {
                uint32_t cb = sb + OFF_CB + (i & 1) * CB, full = bars + (B_CFULL + (i & 1)) * 8;
                mbar_expect_tx(full, 4096);
                bulk_load(cb + CB_P0, g_kvT + (ch0 + 16 * i) * SEQ, 2048, full);
                bulk_load(cb + CB_P0 + CB_PS, g_kvT + (ch0 + 16 * i) * SEQ + 1024, 2048, full);
            };
            mbar_wait(bars + (B_FULL1 + KV_WAIT) * 8, 0);
            mbar_expect_tx(bars + B_KIN * 8, 131 * 160 + 640);
            tma2d(sb + OFF_KT, &tmK, role * 80, m1 * 128 - 3, bars + B_KIN * 8);
            bulk_load(sb + OFF_SK, prm.shift_k + role * 320, 640, bars + B_KIN * 8);
            load_h(0);
            l2_prefetch(prm.gate_w, 1280);
            wait_cnt(C_KV0 + (bid >> 4), 16);
            FENCE_ASYNC_G();
            load_x(0);
            mbar_wait(bars + B_PRE * 8, 0);
            load_h(1);
            wait_cnt(C_KV + (bid >> 4), 16);
            FENCE_ASYNC_G();
            load_x(1);
            for (int i = 0; i < NCH; i++) {
                mbar_wait(bars + (B_CDONE + (i & 1)) * 8, (i >> 1) & 1);
                bulk_store(g_zT + (ch0 + 16 * i) * SEQ, sb + OFF_STG, 4096);
                asm volatile("cp.async.bulk.commit_group;" ::: "memory");
                if (i + 2 < NCH) { load_h(i + 2); load_x(i + 2); }
                asm volatile("cp.async.bulk.wait_group.read 0;" ::: "memory");
                mbar_arrive(bars + B_STG * 8);
                asm volatile("cp.async.bulk.wait_group 0;" ::: "memory");
                FENCE_ASYNC_G();
                signal_cnt_bulk((i < NCH - 1 ? C_Z : C_ZL) + (bid >> 4));
            }
            PROF(12);
        } else if (warp == 2) {
#define PF_WAIT 8
            if (lane == 0 && PF_WAIT < 8) {
                mbar_wait(bars + (B_FULL1 + (PF_WAIT & 3)) * 8, 0);
                if (PF_WAIT >= 4) mbar_wait(bars + (B_FULL1 + (PF_WAIT & 3)) * 8, 1);
                l2_prefetch(prm.wg + bid * 5 * DF, 5 * DF * 2);
                l2_prefetch(prm.wu + bid * 5 * DF, 5 * DF * 2);
                l2_prefetch(prm.x + bid * 16 * DM, 16 * DM * 2);
                l2_prefetch(prm.wd + bid * 8640, 17280);
                l2_prefetch(prm.ssm_k + bid * 5 * SEQ, 5 * SEQ * 2);
            }
            __syncwarp();
            for (int i = 0; i < NCH; i++) {
                const uint32_t cb = sb + OFF_CB + (i & 1) * CB + lane * 16;
                mbar_wait(bars + (B_CRAW + (i & 1)) * 8, (i >> 1) & 1);
                #pragma unroll
                for (int j = 0; j < 8; j++) {
                    uint32_t x0, x1, x2, x3, pv = lds32(cb + CB_HA + j * 512 - 4);
                    asm volatile("ld.shared.v4.u32 {%0,%1,%2,%3}, [%4];" : "=r"(x0), "=r"(x1), "=r"(x2), "=r"(x3) : "r"(cb + CB_HA + j * 512));
                    asm volatile("st.shared.v4.u32 [%0], {%1,%2,%3,%4};" :: "r"(cb + CB_HB + j * 512), "r"(__byte_perm(pv, x0, 0x5432)), "r"(__byte_perm(x0, x1, 0x5432)),
                                 "r"(__byte_perm(x1, x2, 0x5432)), "r"(__byte_perm(x2, x3, 0x5432)) : "memory");
                }
                __syncwarp();
                if (lane == 0) mbar_arrive(bars + (B_CFULL + (i & 1)) * 8);
            }
        } else if (warp == 3 && lane == 0) {
            mbar_wait(bars + B_KV * 8, 0);
            signal_cnt(C_KV0 + role);
            PROF(23);
            mbar_wait(bars + B_KV1 * 8, 0);
            signal_cnt(C_KV + role);
            PROF(14);
            mbar_wait(bars + B_HD * 8, 0);
            signal_cnt(C_H1 + m1);
            if (bid < 120) {
                mbar_wait(bars + B_WD * 8, 0);
                for (int q = 0; q < 3; q++) bulk_store(g_wd + (bid * 9 + q * 3) * 1024, sb + ((2 + q) & 3) * ST1 + 40960, 6144);
                asm volatile("cp.async.bulk.commit_group;" ::: "memory");
                asm volatile("cp.async.bulk.wait_group 0;" ::: "memory");
                FENCE_ASYNC_G();
                signal_cnt_bulk(C_W);
            }
            PROF(15);
            wait_cnt(C_W, 120);
            wait_cnt(C_H1 + m2, 8);
            FENCE_ASYNC_G();
            mbar_wait(bars + B_HD * 8, 1);
            bulk_store(g_h + (m1 * 54 + 32 + 3 * role) * 4096, sb + OFF_HS, role < 7 ? 24576 : 8192);
            bulk_store(g_gate + m1 * 128 + role * 16, sb + OFF_HS + 24576, 64);
            asm volatile("cp.async.bulk.commit_group;" ::: "memory");
            asm volatile("cp.async.bulk.wait_group.read 0;" ::: "memory");
            mbar_expect_tx(bars + (B_FULL2 + 4) * 8, ST2);
            bulk_load(sb + 4 * ST2 + 16384, g_wd + ((cl >> 4) * 27 + 8 + rank) * 10240, 20480, bars + (B_FULL2 + 4) * 8);
            bulk_load(sb + 4 * ST2, g_h + (m2 * 27 + 8 + rank) * 8192, 16384, bars + (B_FULL2 + 4) * 8);
            asm volatile("cp.async.bulk.wait_group 0;" ::: "memory");
            FENCE_ASYNC_G();
            signal_cnt_bulk(C_H2 + m1);
            wait_cnt(C_H2 + m2, 8);
            FENCE_ASYNC_G();
            PROF(9);
            for (int it = 8; it < 14; it++) {
                int st = it < 10 ? it - 5 : it - 10;
                mbar_wait(bars + (B_EMPTY2 + st) * 8, it < 10 ? 0 : 1);
                bulk_load(sb + st * ST2, g_h + (m2 * 27 + (it < 13 ? 2 * it + rank : 26)) * 8192, 16384, bars + (B_FULL2 + st) * 8);
            }
        }
        if (tid == 0) { PROF(13); }
    } else if (wg == 3) {
        asm volatile("setmaxnreg.inc.sync.aligned.u32 168;\n");
        const int t = tid - 384, w = warp & 3;
        const float Dall = lane < NCH ? __bfloat162float(prm.ssm_D[(bid >> 4) * 80 + (bid & 15) + 16 * lane]) : 0.f;
        {
            const int r = lane >> 2, c = lane & 3;
            const int tb = 64 * (w >> 1) + 16 * (r >> 1) + 15 - 8 * (w & 1) - (r & 1);
            const bf16* vp = prm.v + (m1 * 128 + tb) * DM + role * 80 + c * 4;
            uint2 vv[5][4];
            #pragma unroll
            for (int g = 0; g < 5; g++) {
                #pragma unroll
                for (int b = 0; b < 4; b++) asm volatile("ld.global.nc.v2.u32 {%0,%1}, [%2];" : "=r"(vv[g][b].x), "=r"(vv[g][b].y) : "l"(vp - 2 * b * DM + g * 16) : "memory");
            }
            bf16* dst = g_kvT + (role * 80 + 4 * (r >> 1) + (r & 1)) * SEQ + (w & 1) * 1024 + (m1 * 8 + 4 * (w >> 1) + c) * 8;
            const uint32_t ka = sb + OFF_KT + (tb + 3) * 160 + c * 8, wa = sb + OFF_SK + c * 32;
            uint4 sw[2][2];
            uint2 kb[2][10];
            mbar_wait(bars + B_KIN * 8, 0);

            #pragma unroll
            for (int g = -1; g < 5; g++) {
                if (g < 4) {
                    #pragma unroll
                    for (int m = 0; m < 10; m++) asm volatile("ld.shared.v2.u32 {%0,%1}, [%2];" : "=r"(kb[(g + 1) & 1][m].x), "=r"(kb[(g + 1) & 1][m].y) : "r"(ka + (g + 1) * 32 - m * 160));
                    #pragma unroll
                    for (int j = 0; j < 2; j++) asm volatile("ld.shared.v4.u32 {%0,%1,%2,%3}, [%4];" : "=r"(sw[(g + 1) & 1][j].x), "=r"(sw[(g + 1) & 1][j].y), "=r"(sw[(g + 1) & 1][j].z), "=r"(sw[(g + 1) & 1][j].w) : "r"(wa + (g + 1) * 128 + j * 16));
                }
                if (g < 0) continue;
                const uint2* kk = kb[g & 1];
                #pragma unroll
                for (int j = 0; j < 2; j++) {
                    uint32_t s0 = sw[g & 1][j].x, s1 = sw[g & 1][j].y, s2 = sw[g & 1][j].z, s3 = sw[g & 1][j].w, o[4];
                    const uint32_t w0 = __byte_perm(s0, s2, 0x5410), w1 = __byte_perm(s0, s2, 0x7632), w2 = __byte_perm(s1, s3, 0x5410), w3 = __byte_perm(s1, s3, 0x7632);
                    #pragma unroll
                    for (int b = 0; b < 4; b++) {
                        uint32_t a = hmul2(j ? kk[2 * b + 3].y : kk[2 * b + 3].x, w3);
                        a = hfma2(j ? kk[2 * b + 2].y : kk[2 * b + 2].x, w2, a);
                        a = hfma2(j ? kk[2 * b + 1].y : kk[2 * b + 1].x, w1, a);
                        a = hfma2(j ? kk[2 * b].y : kk[2 * b].x, w0, a);
                        a = hmul2(a, j ? vv[g][b].y : vv[g][b].x);
                        asm volatile("movmatrix.sync.aligned.m8n8.trans.b16 %0, %1;" : "=r"(o[b]) : "r"(a));
                    }
                    *(uint4*)(dst + (g * 16 + 2 * j) * SEQ) = make_uint4(o[0], o[1], o[2], o[3]);
                }
                if (g == 0 || g == 4) { __syncwarp(); if (lane == 0) mbar_arrive(bars + (g ? B_KV1 : B_KV) * 8); }

            }
            asm volatile("bar.sync 1, 128;" ::: "memory");

            if (t < 124) { zero_pad(sb + OFF_CB, t); zero_pad(sb + OFF_CB + CB, t); }
            FENCE_ASYNC_S();
            if (t == 127) { mbar_expect_tx(bars + B_G * 8, 1280); bulk_load(sb + OFF_GW, prm.gate_w, 1280, bars + B_G * 8); }
            __syncwarp();
            if (lane == 0) mbar_arrive(bars + B_PRE * 8);
            mbar_wait(bars + B_PRE * 8, 0);
        }

        const int w0 = w & 1, w1 = w >> 1, r = lane >> 2, c = lane & 3;
        const uint32_t a_off = (r & 1) ? CB_HA + 2 * (32 * w1 + 8 * w0 + r - 15 + 2 * c) : CB_HB + 2 * (32 * w1 + 8 * w0 + r - 14 + 2 * c);
        const uint32_t stg = sb + OFF_STG;
        for (int i = 0; i < NCH; i++) {
            const uint32_t cb = sb + OFF_CB + (i & 1) * CB;
            const float Dv = __shfl_sync(0xffffffffu, Dall, i);
            mbar_wait(bars + (B_CFULL + (i & 1)) * 8, (i >> 1) & 1);
            if (t == 0) { PROF(16 + i); }
            float acc[64], t96[48], t64[32], t48[24], t32[16], t16[8];
            uint32_t a0[16], a1[16], a2[16];
            const uint64_t db0 = make_desc(cb + CB_P0, CB_PS, 128, 0);
            const uint32_t aa = cb + a_off;
            conv_loadA(a0, aa + 7 * 512);
            conv_loadA(a1, aa + 6 * 512);
            conv_loadA(a2, aa + 5 * 512);
            conv_group<16, 0>(t16, a0, db0);
            conv_group<32, 0>(t32, a1, db0);
            WG_WAIT(1); AFENCE(a0); conv_loadA(a0, aa + 4 * 512);
            conv_group<48, 0>(t48, a2, db0);
            WG_WAIT(1); AFENCE(a1); conv_loadA(a1, aa + 3 * 512);
            conv_group<64, 0>(t64, a0, db0);
            acc_fence<8>(t16); acc_fence<16>(t32);
            #pragma unroll
            for (int j = 0; j < 8; j++) t32[8 + j] += t16[j];
            WG_WAIT(1); AFENCE(a2); conv_loadA(a2, aa + 2 * 512);
            acc_fence<24>(t48);
            #pragma unroll
            for (int j = 0; j < 16; j++) t48[8 + j] += t32[j];
            WG_WAIT(0); AFENCE(a0);
            #pragma unroll
            for (int j = 0; j < 32; j++) asm volatile("add.f32 %0, %1, %2;" : "=f"(t96[16 + j]) : "f"(t64[j]), "f"(j < 8 ? 0.f : t48[j < 8 ? 0 : j - 8]) : "memory");
            #pragma unroll
            for (int j = 0; j < 16; j++) asm volatile("mov.b32 %0, 0;" : "=f"(t96[j]) :: "memory");
            conv_group<96, 1>(t96, a1, db0 - 16);
            conv_loadA(a0, aa + 1 * 512);
            conv_group<96, 1>(t96, a2, db0);
            WG_WAIT(1); AFENCE(a1); conv_loadA(a1, aa);
            WG_WAIT(0); AFENCE(a2);
            #pragma unroll
            for (int j = 0; j < 48; j++) asm volatile("add.f32 %0, %1, 0f00000000;" : "=f"(acc[16 + j]) : "f"(t96[j]) : "memory");
            #pragma unroll
            for (int j = 0; j < 16; j++) asm volatile("mov.b32 %0, 0;" : "=f"(acc[j]) :: "memory");
            conv_group<128, 1>(acc, a0, db0 - 16);
            conv_group<128, 1>(acc, a1, db0);
            const uint32_t kvp = cb + CB_P0 + (1 - w0) * CB_PS + (7 - r) * 2 + c * 32 + w1 * (8 * 128 + 32);
            uint32_t kq[9];
            #pragma unroll
            for (int q = 0; q < 9; q++) {
                uint16_t u0, u1;
                asm volatile("ld.shared.u16 %0, [%1];" : "=h"(u0) : "r"(kvp + q * 128));
                asm volatile("ld.shared.u16 %0, [%1];" : "=h"(u1) : "r"(kvp + q * 128 + 16));
                kq[q] = (uint32_t)u0 | ((uint32_t)u1 << 16);
            }
            if (w1 && c == 3) kq[7] = 0;
            kq[8] = w1 ? kq[0] : (c ? 0u : kq[8]);
            const uint32_t mlo = w1 ? 0u : 0xFFFFFFFFu;
            WG_WAIT(0);
            AFENCE(a0); AFENCE(a1);
            acc_fence<64>(acc);
            if (t == 0 && i == CI) { PROF(26); }
            #pragma unroll
            for (int q = 15; q >= 0; q--) {
                const uint32_t kk = q < 8 ? (kq[q] & mlo) : (q == 8 ? kq[8] : (kq[q - 8] & ~mlo));
                acc[4 * q] = fmaf(Dv, bf_lo(kk), q ? acc[4 * q] + acc[q ? 4 * q - 2 : 0] : acc[0]);
                acc[4 * q + 1] = fmaf(Dv, bf_hi(kk), q ? acc[4 * q + 1] + acc[q ? 4 * q - 1 : 0] : acc[1]);
            }
            asm volatile("bar.sync 1, 128;" ::: "memory");
            const uint32_t xs1 = cb + CB_HA + w0 * 2048, xs0 = cb + CB_HB + w0 * 2048;
            if (w1 == 0) {
                #pragma unroll
                for (int q = 8; q < 16; q++) sts64f(xs0 + (q - 8) * 256 + lane * 8, acc[4 * q], acc[4 * q + 1]);
            } else {
                #pragma unroll
                for (int q = 0; q < 8; q++) sts64f(xs1 + q * 256 + lane * 8, acc[4 * q], acc[4 * q + 1]);
            }
            if (i > 0) mbar_wait(bars + B_STG * 8, (i - 1) & 1);
            asm volatile("bar.sync 1, 128;" ::: "memory");
            if (t == 0 && i == CI) { PROF(27); }
            uint32_t pk[8];
            if (w1 == 0) {
                const uint32_t rd = xs1 + (c > 0 ? lane * 8 - 8 : lane * 8 + 24 - 256);
                #pragma unroll
                for (int q = 0; q < 9; q++) {
                    float2 o = make_float2(0.f, 0.f);
                    if (q == 0) { if (c > 0) o = lds64f(rd); }
                    else if (q == 8) { if (c == 0) o = lds64f(rd + q * 256); }
                    else o = lds64f(rd + q * 256);
                    float z0 = acc[4 * q] + o.x;
                    float z1 = acc[4 * q + 1] + o.y;
                    uint32_t pz = pack2(z0, z1);
                    if (q < 8) pk[q] = pz;
                    else if (c == 0) {
                        asm volatile("st.shared.u16 [%0], %1;" :: "r"(stg + 64 * 32 + w0 * 16 + r * 2), "h"((uint16_t)(pz & 0xFFFF)) : "memory");
                        asm volatile("st.shared.u16 [%0], %1;" :: "r"(stg + 65 * 32 + w0 * 16 + r * 2), "h"((uint16_t)(pz >> 16)) : "memory");
                    }
                }
                stsm4_t(stg + lane * 32 + w0 * 16, pk[0], pk[1], pk[2], pk[3]);
                stsm4_t(stg + (32 + lane) * 32 + w0 * 16, pk[4], pk[5], pk[6], pk[7]);
            } else {
                const uint32_t rd = xs0 + (c < 3 ? lane * 8 + 8 : lane * 8 - 24 + 256);
                #pragma unroll
                for (int q = 8; q < 16; q++) {
                    float2 o = make_float2(0.f, 0.f);
                    if (q < 15 || c < 3) o = lds64f(rd + (q - 8) * 256);
                    pk[q - 8] = pack2(acc[4 * q] + o.x, acc[4 * q + 1] + o.y);
                }
                stsm4_t(stg + (66 + lane) * 32 + w0 * 16, pk[0], pk[1], pk[2], pk[3]);
                stsm4_t(stg + (98 + lane) * 32 + w0 * 16, pk[4], pk[5], pk[6], pk[7]);
            }
            FENCE_ASYNC_S();
            __syncwarp();
            if (lane == 0) mbar_arrive(bars + (B_CDONE + (i & 1)) * 8);
            if (t == 0 && i == CI) { PROF(28); }
        }
        if (t == 0) { PROF(21); }
    } else {
        asm volatile("setmaxnreg.inc.sync.aligned.u32 160;\n");
        const int cw = wg - 1, t = tid & 127, w = warp & 3, r = lane >> 2, c = lane & 3;
        {
            float d[128];
            if (cw == 1) PP_ARRIVE();
            for (int it = 0; it < 10; it++) {
                int st = it & 3;
                mbar_wait(bars + (B_FULL1 + st) * 8, (it >> 2) & 1);
                if (it == 0 && tid == 128) { PROF(0); }
                uint64_t da = make_desc(sb + st * ST1 + cw * 8192, 16, 1024, 1);
                uint64_t db = make_desc(sb + st * ST1 + 16384, 8192, 1024, 1);
                PP_SYNC();
                WG_FENCE();
                #pragma unroll
                for (int k = 0; k < 4; k++) {
                    wgmma_ss_n128(d, da + k * 2, db + k * 128, (it | k) != 0);
                    wgmma_ss_n128(d + 64, da + k * 2, db + 1024 + k * 128, (it | k) != 0);
                }
                WG_COMMIT();
                PP_ARRIVE();
                WG_WAIT(0);
                if (t < 2) mbar_arrive_cluster(bars + (B_EMPTY1 + st) * 8, t);
            }
            WG_WAIT(0);
            #pragma unroll
            for (int j = 0; j < 128; j++) asm volatile("" : "+f"(d[j]) :: "memory");
            if (tid == 128) { PROF(1); }
            bf16* hrow = g_h + (m1 * 54 + role * 4) * 4096 + cw * 2048 + w * 512 + c * 64 + r * 8;
            #pragma unroll
            for (int G = 0; G < 4; G++) {
                #pragma unroll
                for (int hf = 0; hf < 2; hf++) {
                    uint32_t p[4];
                    #pragma unroll
                    for (int q = 0; q < 4; q++) {
                        int j = (G * 4 + q) * 4 + hf * 2;
                        p[q] = pack2(geglu(d[j], d[64 + j]), geglu(d[j + 1], d[64 + j + 1]));
                    }
                    *(uint4*)(hrow + hf * 256 + G * 4096) = make_uint4(p[0], p[1], p[2], p[3]);
                }
            }
            __syncwarp();
            if (lane == 0) mbar_arrive(bars + B_HD * 8);
            if (tid == 128) { PROF(2); }
            float d2[96];
            const int grow = role * 16 + (warp - 4) * 2 + (lane >> 4);
            const uint32_t gx = sb + grow * 128 + ((((lane >> 1) & 7) ^ (grow & 7)) << 4) + (lane & 1) * 8;
            const uint32_t gwp = sb + OFF_GW + (lane & 15) * 8;
            mbar_wait(bars + B_G * 8, 0);
            float gs = 0.f;
            for (int it = 10; it < 20; it++) {
                int st = it & 3;
                mbar_wait(bars + (B_FULL1 + st) * 8, (it >> 2) & 1);
                uint64_t da = make_desc(sb + st * ST1 + cw * 8192, 16, 1024, 1);
                uint64_t db = make_desc(sb + st * ST1 + 16384, 4096, 512, 2);
                PP_SYNC();
                WG_FENCE();
                #pragma unroll
                for (int k = 0; k < 4; k++) {
                    wgmma_ss_n192(d2, da + k * 2, db + k * 64, ((it - 10) | k) != 0);
                }
                WG_COMMIT();
                PP_ARRIVE();
                uint32_t x0, x1; uint2 gwv;
                asm volatile("ld.shared.v2.u32 {%0,%1}, [%2];" : "=r"(gwv.x), "=r"(gwv.y) : "r"(gwp + ((it - 4 + rot) % 10) * 128));
                asm volatile("ld.shared.v2.u32 {%0,%1}, [%2];" : "=r"(x0), "=r"(x1) : "r"(gx + st * ST1));
                gs = fmaf(bf_lo(x0), bf_lo(gwv.x), fmaf(bf_hi(x0), bf_hi(gwv.x), fmaf(bf_lo(x1), bf_lo(gwv.y), fmaf(bf_hi(x1), bf_hi(gwv.y), gs))));
                asm volatile("bar.sync %0, 128;" :: "r"(4 + cw), "f"(gs) : "memory");
                WG_WAIT(0);
                if (t < 2) mbar_arrive_cluster(bars + (B_EMPTY1 + st) * 8, t);
            }
            #pragma unroll
            for (int o = 1; o < 16; o <<= 1) gs += __shfl_xor_sync(0xffffffffu, gs, o);
            WG_WAIT(0);
            asm volatile("bar.sync 6, 256;" ::: "memory");
            if ((lane & 15) == 0) asm volatile("st.shared.f32 [%0], %1;" :: "r"(sb + OFF_HS + 24576 + (grow & 15) * 4), "f"(1.0f / (1.0f + __expf(-gs))) : "memory");
            #pragma unroll
            for (int j = 0; j < 96; j++) asm volatile("" : "+f"(d2[j]) :: "memory");
            if (tid == 128) { PROF(3); }
            #pragma unroll
            for (int G = 0; G < 3; G++) {
                int Gg = 32 + role * 3 + G;
                if (Gg < DF / 32) {
                    #pragma unroll
                    for (int hf = 0; hf < 2; hf++) {
                        uint32_t p[4];
                        #pragma unroll
                        for (int q = 0; q < 4; q++) {
                            int j = (G * 4 + q) * 4 + hf * 2;
                            p[q] = pack2(geglu(d2[j], d2[48 + j]), geglu(d2[j + 1], d2[48 + j + 1]));
                        }
                        asm volatile("st.shared.v4.u32 [%0], {%1,%2,%3,%4};" :: "r"(sb + OFF_HS + G * 8192 + cw * 4096 + w * 1024 + hf * 512 + c * 128 + r * 16), "r"(p[0]), "r"(p[1]), "r"(p[2]), "r"(p[3]) : "memory");
                    }
                }
            }
            FENCE_ASYNC_S();
            __syncwarp();
            if (lane == 0) mbar_arrive(bars + B_HD * 8);
            if (tid == 128) { PROF(4); }
        }
        float e[40], g0, g1;
        {
            float f[80];
            int st = 0; uint32_t ph = 0;
            for (int it = 0; it < 13; it++) {
                mbar_wait(bars + (B_FULL2 + st) * 8, ph);
                uint64_t da = make_desc(sb + st * ST2 + cw * 4096, 128, 512, 0);
                uint64_t db = make_desc(sb + st * ST2 + 16384, 2048, 256, 3);
                PP_SYNC();
                WG_FENCE();
                #pragma unroll
                for (int k = 0; k < 4; k++) wgmma_ss_n160(f, da + (k & 1) * 16 + (k >> 1) * 512, db + k * 32, (it | k) != 0);
                WG_COMMIT();
#define PP_LATE 3
                if (it >= PP_LATE && (cw == 0 || it < 12)) PP_ARRIVE();
                WG_WAIT(0);
                if (it < PP_LATE && (cw == 0 || it < 12)) PP_ARRIVE();
                if (t == 0) mbar_arrive(bars + (B_EMPTY2 + st) * 8);
                if (it == 11 && t == 32) mbar_arrive_cluster(bars + B_XFREE * 8, rank ^ 1);
                if (++st == NST2) { st = 0; ph ^= 1; }
            }
            WG_WAIT(0);
            #pragma unroll
            for (int j = 0; j < 80; j++) asm volatile("" : "+f"(f[j]) :: "memory");
            if (tid == 128) { PROF(5); }
            asm volatile("ld.global.cg.f32 %0, [%1];" : "=f"(g0) : "l"(&g_gate[m2 * 128 + cw * 64 + w * 16 + r]) : "memory");
            asm volatile("ld.global.cg.f32 %0, [%1];" : "=f"(g1) : "l"(&g_gate[m2 * 128 + cw * 64 + w * 16 + r + 8]) : "memory");
            uint32_t xa = sb + cw * 20480 + t * 16, xb = bars + (B_XF + cw) * 8, ra, rb;
            asm volatile("mapa.shared::cluster.u32 %0, %1, %2;" : "=r"(ra) : "r"(xa), "r"(rank ^ 1));
            asm volatile("mapa.shared::cluster.u32 %0, %1, %2;" : "=r"(rb) : "r"(xb), "r"(rank ^ 1));
            #pragma unroll
            for (int j = 0; j < 40; j++) e[j] = rank ? f[40 + j] : f[j];
            mbar_wait(bars + (B_FULL2 + 3) * 8, 0);
            {
                uint64_t da = make_desc(sb + 3 * ST2 + cw * 4096, 128, 512, 0);
                uint64_t db = make_desc(sb + 3 * ST2 + 16384, 2048, 256, 3);
                WG_FENCE();
                #pragma unroll
                for (int k = 0; k < 4; k++) wgmma_ss_n80(e, da + (k & 1) * 16 + (k >> 1) * 512, db + k * 32, 1);
                WG_COMMIT();
            }
            mbar_wait(bars + B_XFREE * 8, 0);
            #pragma unroll
            for (int j = 0; j < 10; j++) {
                float s0 = rank ? f[4 * j] : f[40 + 4 * j], s1 = rank ? f[4 * j + 1] : f[41 + 4 * j], s2 = rank ? f[4 * j + 2] : f[42 + 4 * j], s3 = rank ? f[4 * j + 3] : f[43 + 4 * j];
                asm volatile("st.async.weak.shared::cluster.mbarrier::complete_tx::bytes.v4.f32 [%0], {%1,%2,%3,%4}, [%5];"
                    :: "r"(ra + j * 2048), "f"(s0), "f"(s1), "f"(s2), "f"(s3), "r"(rb) : "memory");
            }
            WG_WAIT(0);
            acc_fence<40>(e);
            mbar_wait(xb, 0);
            #pragma unroll
            for (int j = 0; j < 10; j++) {
                float s0, s1, s2, s3;
                asm volatile("ld.shared.v4.f32 {%0,%1,%2,%3}, [%4];" : "=f"(s0), "=f"(s1), "=f"(s2), "=f"(s3) : "r"(xa + j * 2048) : "memory");
                e[4 * j] += s0; e[4 * j + 1] += s1; e[4 * j + 2] += s2; e[4 * j + 3] += s3;
            }
        }
        if (tid == 128) { PROF(30); }
        mbar_wait(bars + B_QF * 8, 0);
        const int mi = lane >> 3, l8 = lane & 7;
        const uint32_t qa = sb + OFF_Q + (cw * 64 + w * 16 + (mi & 1) * 8 + l8) * 160 + (mi >> 1) * 16;
        const uint32_t za = sb + OFF_Z + cw * 10240 + ((mi >> 1) * 8 + l8) * 128 + (((2 * w + (mi & 1)) ^ l8) << 4);
        #pragma unroll
        for (int j = 0; j < 10; j += 2) {
            uint32_t qv[4], zv[4], o[4];
            if (j == 8) { mbar_wait(bars + B_ZF * 8, 0); if (tid == 128) { PROF(6); } }
            ldsm4(qa + j * 16, qv);
            ldsm4_t(za + j * 1024, zv);
            #pragma unroll
            for (int u = 0; u < 4; u++) {
                float g = (u & 1) ? g1 : g0;
                int ei = (j + (u >> 1)) * 4 + (u & 1) * 2;
                float b0 = 0.5f * e[ei], b1 = 0.5f * e[ei + 1];
                float a0 = bf_lo(qv[u]) * bf_lo(zv[u]), a1 = bf_hi(qv[u]) * bf_hi(zv[u]);
                o[u] = pack2(fmaf(g, a0 - b0, b0), fmaf(g, a1 - b1, b1));
            }
            stsm4(qa + j * 16, o[0], o[1], o[2], o[3]);
        }
        FENCE_ASYNC_S();
        __syncwarp();
        if (lane == 0) {
            tma2d_store(&tmO, sb + OFF_Q + (cw * 64 + w * 16) * 160, n2 * 80, m2 * 128 + cw * 64 + w * 16);
            asm volatile("cp.async.bulk.commit_group;" ::: "memory");
            asm volatile("cp.async.bulk.wait_group.read 0;" ::: "memory");
        }
        if (tid == 128) { PROF(7); }
    }
}

#define CHK(x) (x)
typedef CUresult (*EncodeFn)(CUtensorMap*, CUtensorMapDataType, cuuint32_t, void*, const cuuint64_t*, const cuuint64_t*, const cuuint32_t*, const cuuint32_t*,
                             CUtensorMapInterleave, CUtensorMapSwizzle, CUtensorMapL2promotion, CUtensorMapFloatOOBfill);
static void mk2d(EncodeFn enc, CUtensorMap* m, const void* p, uint64_t d0, uint64_t d1, uint32_t b0, uint32_t b1, CUtensorMapSwizzle sw) {
    cuuint64_t gd[2] = {d0, d1}; cuuint64_t gs[1] = {d0 * 2}; cuuint32_t bd[2] = {b0, b1}; cuuint32_t es[2] = {1, 1};
    CHK(enc(m, CU_TENSOR_MAP_DATA_TYPE_BFLOAT16, 2, (void*)p, gd, gs, bd, es, CU_TENSOR_MAP_INTERLEAVE_NONE, sw, CU_TENSOR_MAP_L2_PROMOTION_L2_256B, CU_TENSOR_MAP_FLOAT_OOB_FILL_NONE));
}

extern "C" void kernel_launch(void* const* d_in, const int* in_sizes, int n_in, void* d_out, int out_size) {
    static EncodeFn enc = nullptr;
    static void* p_z = nullptr;
    if (!enc) {
        void* fn = nullptr; cudaDriverEntryPointQueryResult qr;
        cudaGetDriverEntryPoint("cuTensorMapEncodeTiled", &fn, cudaEnableDefault, &qr);
        enc = (EncodeFn)fn;
        cudaGetSymbolAddress(&p_z, g_zT);
        cudaFuncSetAttribute(fused_kernel, cudaFuncAttributeMaxDynamicSharedMemorySize, SMEM_TOTAL);
    }
    CUtensorMap tX, tWg, tWu, tWg2, tWu2, tWd, tK, tQ, tZ, tO;
    for (int i = 0; i < 2; i++) {
        cuuint64_t gd[3] = {32, DM, 54}; cuuint64_t gs[2] = {DF * 2, 64}; cuuint32_t bd[3] = {32, 64, 3}; cuuint32_t es[3] = {1, 1, 1};
        CHK(enc(i ? &tWu2 : &tWg2, CU_TENSOR_MAP_DATA_TYPE_BFLOAT16, 3, d_in[7 + i], gd, gs, bd, es, CU_TENSOR_MAP_INTERLEAVE_NONE, CU_TENSOR_MAP_SWIZZLE_64B,
            CU_TENSOR_MAP_L2_PROMOTION_L2_256B, CU_TENSOR_MAP_FLOAT_OOB_FILL_NONE));
    }
    {
        cuuint64_t gd[5] = {DM, 2, 4, 4, 54}; cuuint64_t gs[4] = {1280, 10240, 2560, 40960};
        cuuint32_t bd[5] = {16, 2, 4, 4, 2}; cuuint32_t es[5] = {1, 1, 1, 1, 1};
        CHK(enc(&tWd, CU_TENSOR_MAP_DATA_TYPE_BFLOAT16, 5, d_in[9], gd, gs, bd, es, CU_TENSOR_MAP_INTERLEAVE_NONE, CU_TENSOR_MAP_SWIZZLE_32B,
            CU_TENSOR_MAP_L2_PROMOTION_L2_256B, CU_TENSOR_MAP_FLOAT_OOB_FILL_NONE));
    }
    mk2d(enc, &tK, d_in[1], DM, SEQ, 80, 131, CU_TENSOR_MAP_SWIZZLE_NONE);
    mk2d(enc, &tX, d_in[0], DM, SEQ, 64, 128, CU_TENSOR_MAP_SWIZZLE_128B);
    mk2d(enc, &tWg, d_in[7], DF, DM, 64, 64, CU_TENSOR_MAP_SWIZZLE_128B);
    mk2d(enc, &tWu, d_in[8], DF, DM, 64, 64, CU_TENSOR_MAP_SWIZZLE_128B);
    mk2d(enc, &tQ, d_in[0], DM, SEQ, 80, 128, CU_TENSOR_MAP_SWIZZLE_NONE);
    mk2d(enc, &tZ, p_z, SEQ, DM, 64, 16, CU_TENSOR_MAP_SWIZZLE_128B);
    mk2d(enc, &tO, d_out, DM, SEQ, 80, 16, CU_TENSOR_MAP_SWIZZLE_NONE);
    Params prm;
    prm.x = (const bf16*)d_in[0]; prm.k = (const bf16*)d_in[1]; prm.v = (const bf16*)d_in[2]; prm.shift_k = (const bf16*)d_in[3];
    prm.ssm_k = (const bf16*)d_in[4]; prm.ssm_D = (const bf16*)d_in[5]; prm.gate_w = (const bf16*)d_in[10]; prm.wd = (const bf16*)d_in[9]; prm.wg = (const bf16*)d_in[7]; prm.wu = (const bf16*)d_in[8];
    fused_kernel<<<128, 512, SMEM_TOTAL>>>(tX, tWg, tWu, tWg2, tWu2, tWd, tK, tQ, tZ, tO, prm);
}
```
